```python
import torch

def _softmax(x, axis=-1):
    return torch.softmax(x, dim=axis)
def _gelu(x):
    return torch.nn.functional.gelu(x, approximate="tanh")
def _silu(x):
    return torch.nn.functional.silu(x)
def _sigmoid(x):
    return torch.sigmoid(x)
def _layernorm(x, axis=-1, eps=1e-5):
    m = x.mean(dim=axis, keepdim=True)
    v = x.var(dim=axis, keepdim=True, unbiased=False)
    return (x - m) / torch.sqrt(v + eps)
def _scatter_add(tgt, idx, src, axis=0):
    return tgt.clone().index_add_(axis, idx, src)
def _segment_sum(src, seg, n):
    out = torch.zeros((n,) + src.shape[1:], dtype=src.dtype)
    return out.index_add_(0, seg, src)
def _pad(x, pw):
    flat = tuple(v for pair in reversed(pw) for v in pair)
    return torch.nn.functional.pad(x, flat)

kernel_name = 'parallel_sum__ssm_conv_s4d__moe_arch_mod__prompt'

def setup_inputs():

    _w = (lambda a: (lambda t: t.to(torch.bfloat16) if t.is_floating_point() else t)(torch.as_tensor(a)))
    def _A_setup():
        Bsz, L, D, N = 1, 2048, 1024, 128
        return {
            "u": _w((lambda *s: torch.randn(*s, dtype=torch.bfloat16) * 0.05)(Bsz, L, D)),
            "log_A_real": _w((lambda *s: torch.randn(*s, dtype=torch.bfloat16) * 3.2)(D, N) * 0.5),
            "A_imag": _w((lambda *s: torch.randn(*s, dtype=torch.bfloat16) * 0.2)(D, N) * 3.14),
            "C_real": _w((lambda *s: torch.randn(*s, dtype=torch.bfloat16) * 3.2)(D, N) / N ** 0.5),
            "C_imag": _w((lambda *s: torch.randn(*s, dtype=torch.bfloat16) * 3.2)(D, N) / N ** 0.5),
            "log_dt": _w((lambda *s: torch.randn(*s, dtype=torch.bfloat16) * 0.2)(D) * 0.5 - 4.0),
            "D_skip": _w((lambda *s: torch.randn(*s, dtype=torch.bfloat16) * 0.4)(D)),
        }
    _A_in = _A_setup()

    def _B_setup():
        B, S, D, F, C = 1, 2048, 1024, 3584, 8
        return {
            "x": _w((lambda *s: torch.randn(*s, dtype=torch.bfloat16) * 0.05)(B, S, D)),
            "w_r": _w((lambda *s: torch.randn(*s, dtype=torch.bfloat16) * 0.05)(D)),
            "w_gate": _w((lambda *s: torch.randn(*s, dtype=torch.bfloat16) * 0.05)(D, F)),
            "w_up": _w((lambda *s: torch.randn(*s, dtype=torch.bfloat16) * 0.05)(D, F)),
            "w_down": _w((lambda *s: torch.randn(*s, dtype=torch.bfloat16) * 0.05)(F, D)),
        }
    _B_in = _B_setup()

    return {
        "A_u": _A_in["u"],
        "A_log_A_real": _A_in["log_A_real"],
        "A_A_imag": _A_in["A_imag"],
        "A_C_real": _A_in["C_real"],
        "A_C_imag": _A_in["C_imag"],
        "A_log_dt": _A_in["log_dt"],
        "A_D_skip": _A_in["D_skip"],
        "B_x": _B_in["x"],
        "B_w_r": _B_in["w_r"],
        "B_w_gate": _B_in["w_gate"],
        "B_w_up": _B_in["w_up"],
        "B_w_down": _B_in["w_down"],
    }

def reference(A_u, A_log_A_real, A_A_imag, A_C_real, A_C_imag, A_log_dt, A_D_skip, B_x, B_w_r, B_w_gate, B_w_up, B_w_down):
    def _A_ref(u, log_A_real, A_imag, C_real, C_imag, log_dt, D_skip):
        L = u.shape[1]
        dt = torch.exp(log_dt)
        A = -torch.exp(log_A_real) + 1j * A_imag
        C = (C_real + 1j * C_imag) * dt[:, None]
        pos = (lambda x, dt: x.to(dt))(torch.arange(L), log_dt.dtype)
        P = torch.exp((A * dt[:, None])[:, :, None] * pos[None, None, :])
        K = 2.0 * torch.einsum("dn,dnl->dl", C, P).real
        L2 = 2 * L
        u_t = (lambda x, *d: x.permute(*d))(u, 0, 2, 1)
        Kf = (lambda x, *a, **k: torch.fft.rfft(x.float(), *a, **k))(K, L2)
        Uf = (lambda x, *a, **k: torch.fft.rfft(x.float(), *a, **k))(u_t, L2)
        y = (lambda x, *a, **k: torch.fft.irfft(x, *a, **k).to(torch.bfloat16))(Uf * Kf[None, :, :], L2)[:, :, :L]
        y = (lambda x, *d: x.permute(*d))(y, 0, 2, 1)
        return y + u * D_skip[None, None, :]

    def _B_ref(x, w_r, w_gate, w_up, w_down):
        B, S, D = x.shape
        C = 8
        r = x @ w_r
        idx = torch.argsort(-r, axis=-1)[:, :C]
        idx_e = (lambda x, n, axis: torch.repeat_interleave(x, n, dim=axis))(idx.reshape(B, C, 1), D, axis=2)
        x_sel = (lambda x, i, axis: torch.take_along_dim(x, i, dim=axis))(x, idx_e, axis=1)
        g = _silu(x_sel @ w_gate)
        u = x_sel @ w_up
        y = (g * u) @ w_down
        r_sel = _sigmoid((lambda x, i, axis: torch.take_along_dim(x, i, dim=axis))(r, idx, axis=1))
        y = y * r_sel.reshape(B, C, 1)
        b_off = (torch.arange(B) * S).reshape(B, 1)
        flat_idx = (idx + b_off).reshape(B * C)
        zero = (x * 0.0).reshape(B * S, D)
        upd = _scatter_add(zero, flat_idx, y.reshape(B * C, D), axis=0)
        return x + upd.reshape(B, S, D)

    x = A_u
    xn = _layernorm(x, axis=-1)
    return x + _A_ref(xn, A_log_A_real, A_A_imag, A_C_real, A_C_imag, A_log_dt, A_D_skip) + _B_ref(xn, B_w_r, B_w_gate, B_w_up, B_w_down)
```

```cpp
#include <cuda_runtime.h>
#include <cuda_bf16.h>
#include <cuda_fp16.h>
#include <cuda.h>
#include <stdint.h>

namespace {

constexpr int SEQ = 2048, DM = 1024, NMODE = 128, FF = 3584;
constexpr int NCTA = 128, NTHR = 448;
constexpr int GU_CTAS = 112;

constexpr int OFF_X = 0;
constexpr int OFF_RING = 65536;
constexpr int ROW_PITCH = 2064;
constexpr int OFF_ROWS = OFF_RING + 32768;
constexpr int OFF_XS = OFF_RING + 65536;
constexpr int OFF_PRIV = OFF_XS + 8 * ROW_PITCH;
constexpr int PRIV = 8720;
constexpr int OFF_GP = OFF_PRIV + 8 * PRIV;
constexpr int OFF_BAR = OFF_GP + 8192;
constexpr int OFF_MISC = OFF_BAR + 336;
constexpr int OFF_STAMP = OFF_MISC + 16;
constexpr int SMEM_BYTES = OFF_STAMP;

constexpr int B_X = 0, B_FULL = 8, B_EMPTY = 16, B_VT = 24, B_PV = 25, B_RECV = 26, B_XS = 28, B_DONE = 29, B_ST = 30, B_ROW = 32, B_WR = 36, B_GATE = 37;

constexpr int T_DENSE = 4368;
constexpr int T_PATCH = T_DENSE + 2176;
constexpr int T_S4 = T_PATCH + 96;
constexpr int T_S8 = T_S4 + 736;
constexpr int REC = 272;

#define KG_UNROLL 1
constexpr int KGU = KG_UNROLL;
constexpr uint32_t SPIN_LIMIT = 1u << 22;
#define ROW_DELAY 400
#define STAT_SLEEP 100
#define ORDER 0
#define GATE_KS 1
#define H_SLEEP 100
#define X_DELAY 2500
#define PF_START 3300
#define PF_PERIOD 539
#define LD_START 5500
#define WD_START (PF_START + 17 * PF_PERIOD + 800)
#define WD_PERIOD (PF_PERIOD / 7 * 8)
#define LD_PERIOD 510

constexpr int S_STAT = 0;
constexpr int S_KEY = S_STAT + 8192;
constexpr int S_SEL = S_KEY + 2048;
constexpr int S_EPOCH = S_SEL + 128;
constexpr int S_H = S_EPOCH + 32;
constexpr int S_Y = S_H + 2 * GU_CTAS * 128;
constexpr int S_END = S_Y + 64 * 1024;
__device__ __align__(1024) uint32_t g_scr[S_END];

struct Ptrs {
    const __nv_bfloat16 *logA, *Aim, *Cre, *Cim, *ldt, *dsk, *u, *wr;
    uint32_t* scr;
    const __nv_bfloat16 *wg, *wu, *wd;
    __nv_bfloat16* out;
    uint32_t up_first;
    uint32_t zero;
};
struct Maps {
    CUtensorMap rows, u, out, wgu, wd;
};

__device__ __forceinline__ uint32_t clk() { uint32_t c; asm volatile("mov.u32 %0, %%clock;" : "=r"(c)); return c; }
#define STAMP(i) do { } while (0)
#define GSTAMP(i) do { } while (0)

__device__ __forceinline__ uint32_t s_u32(const void* p) { return (uint32_t)__cvta_generic_to_shared(p); }
__device__ __forceinline__ void mbar_init(uint32_t b, uint32_t n) {
    asm volatile("mbarrier.init.shared::cta.b64 [%0], %1;" ::"r"(b), "r"(n) : "memory");
}
__device__ __forceinline__ void mbar_expect_tx(uint32_t b, uint32_t bytes) {
    asm volatile("mbarrier.arrive.expect_tx.shared::cta.b64 _, [%0], %1;" ::"r"(b), "r"(bytes) : "memory");
}
__device__ __forceinline__ void mbar_arrive(uint32_t b) {
    asm volatile("mbarrier.arrive.shared::cta.b64 _, [%0];" ::"r"(b) : "memory");
}
__device__ __forceinline__ void mbar_arrive_peer(uint32_t b_cluster) {
    asm volatile("mbarrier.arrive.relaxed.cluster.shared::cluster.b64 _, [%0];" ::"r"(b_cluster) : "memory");
}
__device__ __forceinline__ void mbar_wait(uint32_t b, uint32_t parity) {
    asm volatile("{\n\t.reg .pred p;\nW:\n\tmbarrier.try_wait.parity.shared::cta.b64 p, [%0], %1;\n\t@!p bra W;\n\t}" ::"r"(b), "r"(parity) : "memory");
}
__device__ __forceinline__ void mbar_wait_bounded(uint32_t b, uint32_t parity) {
    asm volatile("{\n\t.reg .pred p;\n\t.reg .u32 c;\n\tmov.u32 c, 0;\n"
                 "W:\n\tmbarrier.try_wait.parity.shared::cta.b64 p, [%0], %1, 4000;\n\t@p bra D;\n\t"
                 "add.u32 c, c, 1;\n\tsetp.lt.u32 p, c, 1048576;\n\t@p bra W;\n\ttrap;\nD:\n\t}"
                 ::"r"(b), "r"(parity) : "memory");
}
__device__ __forceinline__ bool elect_one() {
    uint32_t p;
    asm volatile("{ .reg .pred P; elect.sync _|P, 0xffffffff; selp.u32 %0, 1, 0, P; }" : "=r"(p));
    return p != 0;
}
__device__ __forceinline__ uint32_t mapa(uint32_t a, uint32_t rank) {
    uint32_t r;
    asm("mapa.shared::cluster.u32 %0, %1, %2;" : "=r"(r) : "r"(a), "r"(rank));
    return r;
}
__device__ __forceinline__ void cluster_arrive() { asm volatile("barrier.cluster.arrive.relaxed.aligned;" ::: "memory"); }
__device__ __forceinline__ void cluster_wait() { asm volatile("barrier.cluster.wait.aligned;" ::: "memory"); }
__device__ __forceinline__ void tma_load_3d(uint32_t dst, const CUtensorMap* m, int c1, int c2, uint32_t bar) {
    asm volatile("cp.async.bulk.tensor.3d.shared::cluster.global.mbarrier::complete_tx::bytes [%0], [%1, {%3, %4, %5}], [%2];"
                 ::"r"(dst), "l"(m), "r"(bar), "r"(0), "r"(c1), "r"(c2) : "memory");
}
__device__ __forceinline__ void tma_load_4d(uint32_t dst, const CUtensorMap* m, int c0, int c3, uint32_t bar) {
    asm volatile("cp.async.bulk.tensor.4d.shared::cluster.global.mbarrier::complete_tx::bytes [%0], [%1, {%3, %5, %5, %4}], [%2];"
                 ::"r"(dst), "l"(m), "r"(bar), "r"(c0), "r"(c3), "r"(0) : "memory");
}
__device__ __forceinline__ void wait_until(uint32_t t) {
    asm volatile("{\n\t.reg .pred p;\n\t.reg .s32 c;\nW:\n\tmov.u32 c, %%clock;\n\tsub.s32 c, c, %0;\n\tsetp.lt.s32 p, c, 0;\n\t@p nanosleep.u32 40;\n\t@p bra W;\n\t}" ::"r"(t) : "memory");
}
__device__ __forceinline__ void tma_load_4d_both(uint32_t dst, const CUtensorMap* m, int c0, int c3, uint32_t bar) {
    asm volatile("cp.async.bulk.tensor.4d.shared::cluster.global.mbarrier::complete_tx::bytes.multicast::cluster [%0], [%1, {%3, %6, %6, %4}], [%2], %5;"
                 ::"r"(dst), "l"(m), "r"(bar), "r"(c0), "r"(c3), "h"((uint16_t)3), "r"(0) : "memory");
}
__device__ __forceinline__ void tma_store_4d(const CUtensorMap* m, uint32_t src, int c0, int c3) {
    asm volatile("cp.async.bulk.tensor.4d.global.shared::cta.bulk_group [%0, {%2, %4, %4, %3}], [%1];"
                 ::"l"(m), "r"(src), "r"(c0), "r"(c3), "r"(0) : "memory");
}
__device__ __forceinline__ void bulk_g2s(uint32_t dst, const void* src, uint32_t bytes, uint32_t bar) {
    asm volatile("cp.async.bulk.shared::cluster.global.mbarrier::complete_tx::bytes [%0], [%1], %2, [%3];"
                 ::"r"(dst), "l"(src), "r"(bytes), "r"(bar) : "memory");
}
__device__ __forceinline__ void bulk_s2peer(uint32_t dst_cluster, uint32_t src, uint32_t bytes, uint32_t bar_cluster) {
    asm volatile("cp.async.bulk.shared::cluster.shared::cta.mbarrier::complete_tx::bytes [%0], [%1], %2, [%3];"
                 ::"r"(dst_cluster), "r"(src), "r"(bytes), "r"(bar_cluster) : "memory");
}
__device__ __forceinline__ void fence_async() { asm volatile("fence.proxy.async.shared::cta;" ::: "memory"); }
__device__ __forceinline__ void named_sync(int id, int n) { asm volatile("bar.sync %0, %1;" ::"r"(id), "r"(n) : "memory"); }

__device__ __forceinline__ void ldsm4(uint32_t* r, uint32_t a) {
    asm volatile("ldmatrix.sync.aligned.m8n8.x4.shared.b16 {%0,%1,%2,%3}, [%4];"
                 : "=r"(r[0]), "=r"(r[1]), "=r"(r[2]), "=r"(r[3]) : "r"(a));
}
__device__ __forceinline__ void ldsm4t(uint32_t* r, uint32_t a) {
    asm volatile("ldmatrix.sync.aligned.m8n8.x4.trans.shared.b16 {%0,%1,%2,%3}, [%4];"
                 : "=r"(r[0]), "=r"(r[1]), "=r"(r[2]), "=r"(r[3]) : "r"(a));
}
__device__ __forceinline__ void stsm4t(uint32_t a, const uint32_t* r) {
    asm volatile("stmatrix.sync.aligned.m8n8.x4.trans.shared.b16 [%0], {%1,%2,%3,%4};"
                 ::"r"(a), "r"(r[0]), "r"(r[1]), "r"(r[2]), "r"(r[3]) : "memory");
}
__device__ __forceinline__ uint32_t lds32(uint32_t a) { uint32_t v; asm volatile("ld.shared.u32 %0, [%1];" : "=r"(v) : "r"(a)); return v; }
__device__ __forceinline__ uint32_t lds32v(uint32_t a) { uint32_t v; asm volatile("ld.volatile.shared.u32 %0, [%1];" : "=r"(v) : "r"(a)); return v; }
__device__ __forceinline__ float lds32f(uint32_t a) { float v; asm volatile("ld.shared.f32 %0, [%1];" : "=f"(v) : "r"(a)); return v; }
__device__ __forceinline__ uint2 lds64(uint32_t a) { uint2 v; asm volatile("ld.shared.v2.u32 {%0,%1}, [%2];" : "=r"(v.x), "=r"(v.y) : "r"(a)); return v; }
__device__ __forceinline__ uint4 lds128(uint32_t a) {
    uint4 v; asm volatile("ld.shared.v4.u32 {%0,%1,%2,%3}, [%4];" : "=r"(v.x), "=r"(v.y), "=r"(v.z), "=r"(v.w) : "r"(a)); return v;
}
__device__ __forceinline__ void sts16(uint32_t a, uint32_t v) { asm volatile("st.shared.u16 [%0], %1;" ::"r"(a), "r"(v) : "memory"); }
__device__ __forceinline__ void sts32(uint32_t a, uint32_t v) { asm volatile("st.shared.u32 [%0], %1;" ::"r"(a), "r"(v) : "memory"); }
__device__ __forceinline__ void sts64(uint32_t a, uint32_t x, uint32_t y) { asm volatile("st.shared.v2.u32 [%0], {%1,%2};" ::"r"(a), "r"(x), "r"(y) : "memory"); }
__device__ __forceinline__ void sts128(uint32_t a, uint32_t x, uint32_t y, uint32_t z, uint32_t w) {
    asm volatile("st.shared.v4.u32 [%0], {%1,%2,%3,%4};" ::"r"(a), "r"(x), "r"(y), "r"(z), "r"(w) : "memory");
}
__device__ __forceinline__ void sts128f(uint32_t a, const float* c) {
    asm volatile("st.shared.v4.f32 [%0], {%1,%2,%3,%4};" ::"r"(a), "f"(c[0]), "f"(c[1]), "f"(c[2]), "f"(c[3]) : "memory");
}
__device__ __forceinline__ uint2 ldg64(const void* p) {
    uint2 v; asm volatile("ld.global.nc.L1::no_allocate.v2.u32 {%0,%1}, [%2];" : "=r"(v.x), "=r"(v.y) : "l"(p)); return v;
}
__device__ __forceinline__ uint32_t ldg16(const void* p) {
    uint16_t v; asm volatile("ld.global.nc.u16 %0, [%1];" : "=h"(v) : "l"(p)); return v;
}
__device__ __forceinline__ uint32_t ld_relaxed_32(const void* p) {
    uint32_t v; asm volatile("ld.relaxed.gpu.global.u32 %0, [%1];" : "=r"(v) : "l"(p) : "memory"); return v;
}
__device__ __forceinline__ uint2 ld_relaxed_64(const void* p) {
    uint2 v; asm volatile("ld.relaxed.gpu.global.v2.u32 {%0,%1}, [%2];" : "=r"(v.x), "=r"(v.y) : "l"(p) : "memory"); return v;
}
__device__ __forceinline__ uint4 ld_relaxed_128(const void* p) {
    uint4 v; asm volatile("ld.relaxed.gpu.global.v4.u32 {%0,%1,%2,%3}, [%4];" : "=r"(v.x), "=r"(v.y), "=r"(v.z), "=r"(v.w) : "l"(p) : "memory"); return v;
}
__device__ __forceinline__ void st_relaxed_32(void* p, uint32_t v) {
    asm volatile("st.relaxed.gpu.global.u32 [%0], %1;" ::"l"(p), "r"(v) : "memory");
}
__device__ __forceinline__ void st_relaxed_128(void* p, uint32_t x, uint32_t y, uint32_t z, uint32_t w) {
    asm volatile("st.relaxed.gpu.global.v4.u32 [%0], {%1,%2,%3,%4};" ::"l"(p), "r"(x), "r"(y), "r"(z), "r"(w) : "memory");
}
__device__ __forceinline__ void st_relaxed_64(void* p, uint32_t x, uint32_t y) {
    asm volatile("st.relaxed.gpu.global.u64 [%0], %1;" ::"l"(p), "l"((unsigned long long)x | ((unsigned long long)y << 32)) : "memory");
}
__device__ __forceinline__ void mma_bf16(float* c, uint32_t a0, uint32_t a1, uint32_t a2, uint32_t a3, uint32_t b0, uint32_t b1) {
    asm("mma.sync.aligned.m16n8k16.row.col.f32.bf16.bf16.f32 {%0,%1,%2,%3}, {%4,%5,%6,%7}, {%8,%9}, {%0,%1,%2,%3};"
                 : "+f"(c[0]), "+f"(c[1]), "+f"(c[2]), "+f"(c[3]) : "r"(a0), "r"(a1), "r"(a2), "r"(a3), "r"(b0), "r"(b1));
}
__device__ __forceinline__ void mma_bf16_z(float* c, uint32_t a0, uint32_t a1, uint32_t a2, uint32_t a3, uint32_t b0, uint32_t b1) {
    asm("mma.sync.aligned.m16n8k16.row.col.f32.bf16.bf16.f32 {%0,%1,%2,%3}, {%4,%5,%6,%7}, {%8,%9}, {%10,%10,%10,%10};"
        : "=f"(c[0]), "=f"(c[1]), "=f"(c[2]), "=f"(c[3]) : "r"(a0), "r"(a1), "r"(a2), "r"(a3), "r"(b0), "r"(b1), "f"(0.f));
}
__device__ __forceinline__ void mma_f16(float* c, const uint4& a, uint32_t b0, uint32_t b1) {
    asm("mma.sync.aligned.m16n8k16.row.col.f32.f16.f16.f32 {%0,%1,%2,%3}, {%4,%5,%6,%7}, {%8,%9}, {%0,%1,%2,%3};"
                 : "+f"(c[0]), "+f"(c[1]), "+f"(c[2]), "+f"(c[3]) : "r"(a.x), "r"(a.y), "r"(a.z), "r"(a.w), "r"(b0), "r"(b1));
}
__device__ __forceinline__ uint32_t pack_bf16(float lo, float hi) {
    uint32_t r; asm("cvt.rn.bf16x2.f32 %0, %1, %2;" : "=r"(r) : "f"(hi), "f"(lo)); return r;
}
__device__ __forceinline__ uint32_t pack_bf16v(float lo, float hi) {
    uint32_t r; asm volatile("cvt.rn.bf16x2.f32 %0, %1, %2;" : "=r"(r) : "f"(hi), "f"(lo)); return r;
}
__device__ __forceinline__ uint32_t pack_f16(float lo, float hi) {
    uint32_t r; asm("cvt.rn.f16x2.f32 %0, %1, %2;" : "=r"(r) : "f"(hi), "f"(lo)); return r;
}
__device__ __forceinline__ float bf_lo(uint32_t v) { return __uint_as_float(v << 16); }
__device__ __forceinline__ float bf_hi(uint32_t v) { return __uint_as_float(v & 0xffff0000u); }
__device__ __forceinline__ float bf_round(float x) { return __uint_as_float(pack_bf16(0.f, x)); }
__device__ __forceinline__ __nv_bfloat162 as_b2(uint32_t x) { return *reinterpret_cast<__nv_bfloat162*>(&x); }
__device__ __forceinline__ uint32_t as_u(__nv_bfloat162 x) { return *reinterpret_cast<uint32_t*>(&x); }
__device__ __forceinline__ uint32_t badd2(uint32_t a, uint32_t b) { uint32_t r; asm("add.rn.bf16x2 %0, %1, %2;" : "=r"(r) : "r"(a), "r"(b)); return r; }
__device__ __forceinline__ float rcpf(float x) { float r; asm("rcp.approx.ftz.f32 %0, %1;" : "=f"(r) : "f"(x)); return r; }
__device__ __forceinline__ float sqrtaf(float x) { float r; asm("sqrt.approx.ftz.f32 %0, %1;" : "=f"(r) : "f"(x)); return r; }
__device__ __forceinline__ float ex2f(float x) { float r; asm("ex2.approx.ftz.f32 %0, %1;" : "=f"(r) : "f"(x)); return r; }
constexpr float L2E = 1.4426950408889634f;
constexpr uint32_t ONES = 0x3f803f80u;

__device__ __forceinline__ uint2 recip2(uint32_t s2) {
    const uint32_t hi = pack_bf16(rcpf(bf_lo(s2)), rcpf(bf_hi(s2)));
    return make_uint2(hi, as_u(__hmul2(__hfma2(__hneg2(as_b2(s2)), as_b2(hi), as_b2(ONES)), as_b2(hi))));
}
__device__ __forceinline__ uint32_t normalize2(uint32_t x, __nv_bfloat162 m, __nv_bfloat162 rh, __nv_bfloat162 rl) {
    const __nv_bfloat162 d = __hsub2(as_b2(x), m);
    return as_u(__hfma2(d, rh, __hmul2(d, rl)));
}

__device__ __forceinline__ uint32_t order_key(uint32_t b16) { return b16 ^ ((b16 & 0x8000u) ? 0xffffu : 0x8000u); }
__device__ __forceinline__ uint32_t unorder_key(uint32_t k16) { return k16 ^ ((k16 & 0x8000u) ? 0x8000u : 0xffffu); }

struct cplx { float r, i; };
__device__ __forceinline__ cplx csq(cplx a) { return {a.r * a.r - a.i * a.i, (a.r + a.r) * a.i}; }
__device__ __forceinline__ cplx cexpp(float a2, float th) {
    float m = ex2f(a2), s, c;
    __sincosf(th, &s, &c);
    return {m * c, m * s};
}
struct hc { __half2 r, i; };
__device__ __forceinline__ __half2 as_h2(uint32_t x) { return *reinterpret_cast<__half2*>(&x); }
__device__ __forceinline__ uint32_t as_u(__half2 x) { return *reinterpret_cast<uint32_t*>(&x); }
__device__ __forceinline__ hc hmul(hc a, hc b) {
    return {__hfma2(a.r, b.r, __hneg2(__hmul2(a.i, b.i))), __hfma2(a.r, b.i, __hmul2(a.i, b.r))};
}
__device__ __forceinline__ hc hsq_conj(hc a) {
    const __half2 t = __hmul2(a.r, a.i);
    return {__hfma2(a.r, a.r, __hneg2(__hmul2(a.i, a.i))), __hsub2(__hneg2(t), t)};
}
__device__ __forceinline__ hc hpack(cplx a, cplx b) { return {as_h2(pack_f16(a.r, b.r)), as_h2(pack_f16(a.i, b.i))}; }
__device__ __forceinline__ void st_pair(uint32_t a, hc x, hc y) { sts128(a, as_u(x.r), as_u(x.i), as_u(y.r), as_u(y.i)); }
__device__ __forceinline__ void st_quad(uint32_t a, hc x, hc y) { sts128(a, as_u(x.r), as_u(y.r), as_u(x.i), as_u(y.i)); }

__device__ __forceinline__ void kgen_mma(float (&acc)[5][4], uint32_t priv, int lane, uint2 la, uint2 aim, uint2 cre, uint2 cim, float dt, uint32_t cs2) {
    const int g = lane >> 2, t = lane & 3;
#pragma unroll
    for (int i = 0; i < 5; i++) { acc[i][0] = acc[i][1] = acc[i][2] = acc[i][3] = 0.f; }
    const uint32_t wr = priv + lane * REC, rd = priv + 2 * t * REC;
    const float ndl = -dt * L2E;
#pragma unroll 1
    for (int ps = 0; ps < 2; ps++) {
        const uint32_t lw = ps ? la.y : la.x, iw = ps ? aim.y : aim.x;
        const uint32_t crw = as_u(__hmul2(as_b2(ps ? cre.y : cre.x), as_b2(cs2))), ciw = as_u(__hmul2(as_b2(ps ? cim.y : cim.x), as_b2(cs2)));
        const uint32_t ap = pack_bf16(ex2f(bf_lo(lw) * L2E), ex2f(bf_hi(lw) * L2E));
        const float a2[2] = {bf_lo(ap) * ndl, bf_hi(ap) * ndl}, th[2] = {bf_lo(iw) * dt, bf_hi(iw) * dt};
        cplx p1[2], p2[2], p4[2], p16[2], p32[2], p64[2], p256[2], p512[2];
#pragma unroll
        for (int i = 0; i < 2; i++) {
            p1[i] = cexpp(a2[i], th[i]); p16[i] = cexpp(a2[i] * 16.f, th[i] * -16.f); p256[i] = cexpp(a2[i] * 256.f, th[i] * 256.f);
            p2[i] = csq(p1[i]); p4[i] = csq(p2[i]); p32[i] = csq(p16[i]); p64[i] = csq(p32[i]); p512[i] = csq(p256[i]);
        }
        const hc C = {as_h2(pack_f16(bf_lo(crw), bf_hi(crw))), as_h2(pack_f16(bf_lo(ciw), bf_hi(ciw)))};
        const hc z1 = hpack(p1[0], p1[1]), z2 = hpack(p2[0], p2[1]), z4 = hpack(p4[0], p4[1]);
        const hc y16 = hpack(p16[0], p16[1]), y32 = hpack(p32[0], p32[1]), y64 = hpack(p64[0], p64[1]);
        const hc z256 = hpack(p256[0], p256[1]), z512 = hpack(p512[0], p512[1]);
        const hc y8 = hsq_conj(z4), z128 = hsq_conj(y64), z1024 = hmul(z512, z512);
        __syncwarp();
        const hc y48 = hmul(y16, y32), y24 = hmul(y16, y8), y40 = hmul(y32, y8), y56 = hmul(y48, y8);
        st_quad(wr, {as_h2(0x3c003c00u), as_h2(0u)}, y8);
        st_quad(wr + 16, y16, y24);
        st_quad(wr + 32, y32, y40);
        st_quad(wr + 48, y48, y56);
        st_quad(wr + 64, y64, hmul(y64, y8));
        st_quad(wr + 80, hmul(y64, y16), hmul(y64, y24));
        st_quad(wr + 96, hmul(y64, y32), hmul(y64, y40));
        st_quad(wr + 112, hmul(y64, y48), hmul(y64, y56));
        const hc c1 = hmul(C, z1), c2 = hmul(C, z2), c5 = hmul(c1, z4), c6 = hmul(c2, z4);
        st_pair(wr + 128, c1, c2);
        st_pair(wr + 144, c5, c6);
        st_pair(wr + 160, hmul(c1, z128), hmul(c2, z128));
        st_pair(wr + 176, hmul(c5, z128), hmul(c6, z128));
        const hc z258 = hmul(z256, z2);
        st_pair(wr + 192, hmul(z256, z1), z258);
        st_pair(wr + 208, z258, z512);
        st_pair(wr + 224, z2, hmul(z512, z4));
        st_pair(wr + 240, z2, z1024);
        __syncwarp();
#pragma unroll KGU
        for (int k2 = 0; k2 < 4; k2++) {
#pragma unroll
            for (int s = 0; s < 2; s++) {
                const uint32_t o = rd + k2 * 8 * REC + s * REC;
                const uint4 A = lds128(o + 16 * g);
                const uint2 h = lds64(o + 128 + 8 * g);
                const uint4 M = lds128(o + 192 + 16 * (g & 1)), N = lds128(o + 224 + 8 * (g & 2));
                const hc H0 = {as_h2(h.x), as_h2(h.y)};
                const hc H1 = hmul(H0, {as_h2(N.x), as_h2(N.y)}), H2 = hmul(H0, {as_h2(M.x), as_h2(M.y)});
                const hc H3 = hmul(H2, {as_h2(M.z), as_h2(M.w)}), H4 = hmul(H3, {as_h2(N.z), as_h2(N.w)});
                mma_f16(acc[0], A, h.x, h.y);
                mma_f16(acc[1], A, as_u(H1.r), as_u(H1.i));
                mma_f16(acc[2], A, as_u(H2.r), as_u(H2.i));
                mma_f16(acc[3], A, as_u(H3.r), as_u(H3.i));
                mma_f16(acc[4], A, as_u(H4.r), as_u(H4.i));
            }
        }
    }
}

__device__ __forceinline__ void kgen_tables(const float (&acc)[5][4], uint32_t priv, int lane, float scale, float k0) {
    const int g = lane >> 2, t0 = lane & 1, t1 = (lane >> 1) & 1;
    __syncwarp();
#pragma unroll
    for (int i = 0; i < 3; i++) sts128(priv + T_PATCH - 64 + 512 * i + 16 * lane, 0, 0, 0, 0);
    if (lane < 20) sts128(priv + 16 * lane + (lane < 16 ? 0 : T_DENSE - 256), 0, 0, 0, 0);
    const uint32_t pd = priv + T_DENSE + 64 + 512 * t1 + 64 * g + 16 * t0;
    uint32_t w4[2];
#pragma unroll
    for (int hf = 0; hf < 2; hf++) {
        const float k1 = acc[0][2 * hf] * scale, k2 = acc[0][2 * hf + 1] * scale, k3 = acc[1][2 * hf] * scale, k4 = acc[1][2 * hf + 1] * scale;
        w4[hf] = pack_bf16(k4, k3);
        sts128(pd + 32 * hf, pack_bf16(k1, 0.f), pack_bf16(k2, k1), pack_bf16(k3, k2), w4[hf]);
    }
    __syncwarp();
    const uint32_t p4 = priv + T_S4 + 16 * (6 + g + 8 * t1) + 4 * (t0 ^ 1), p8 = priv + T_S8 + 8 * (6 + g + 8 * t1 + 32 * t0);
    uint32_t aa, c3;
#pragma unroll
    for (int hf = 0; hf < 2; hf++) {
        sts16(pd + 32 * hf + 18, w4[hf]);
        const float b = acc[2][2 * hf] * scale, a = acc[2][2 * hf + 1] * scale;
        aa = pack_bf16(a, a);
        sts16(pd + 1024 + 32 * hf + 4, pack_bf16(b, b));
        sts64(pd + 1024 + 32 * hf + 8, pack_bf16(a, b), aa);
        sts32(pd + 1024 + 32 * hf + 16, aa);
        sts16(pd + 1024 + 32 * hf + 22, aa);
#pragma unroll
        for (int e = 0; e < 2; e++) {
            const float x3 = acc[3][2 * hf + e] * scale, x4 = acc[4][2 * hf + e] * scale;
            c3 = pack_bf16(x3, x3);
            const uint32_t c4 = pack_bf16(x4, x4);
            sts16(p4 + 256 * e + 8 * hf, c3); sts16(p4 + 256 * e + 8 * hf + 18, c3);
            sts16(p8 + 128 * e + 4 * hf, c4); sts16(p8 + 128 * e + 4 * hf + 10, c4);
        }
    }
    if (lane == 31) {
        const uint32_t pe = priv + T_DENSE + 60, kk = pack_bf16(k0, k0);
        sts16(pe, kk); sts16(pe + 6, kk);
        sts16(pe + 4 * 257, w4[1]); sts16(pe + 4 * 258 + 2, w4[1]);
        sts16(pe + 4 * 514, aa); sts16(pe + 4 * 515 + 2, aa);
        sts16(priv + T_PATCH + 36, c3); sts32(priv + T_PATCH + 40, c3); sts16(priv + T_PATCH + 46, c3);
    }
    __syncwarp();
}

__device__ __forceinline__ void dense_phase(float (&acc)[16][4], uint32_t priv, uint32_t gate, int lane) {
    const int m = lane >> 3, r = lane & 7;
    const uint32_t vrow = priv + 256;
    const uint32_t pb = priv + T_DENSE + 4 * (15 + (lane >> 2) - 2 * (lane & 3));
    {
        const int lam = 8 * (lane >> 4) + r;
        const uint32_t a = vrow + lam * 32 + (((m & 1) ^ (r >> 2)) << 4);
        const uint32_t a0 = lds32(pb), a1 = lds32(pb + 32), a2 = lds32(pb - 32), a3 = lds32v(pb);
        const uint32_t pp = pb + T_PATCH - T_DENSE - 36;
        const uint32_t n0 = lds32(pp), n1 = lds32(pp + 32), n3 = lds32v(pp);
#pragma unroll
        for (int i = 7; i >= 0; i--) {
            uint32_t R[4];
            ldsm4(R, a + i * 512);
            mma_bf16_z(acc[2 * i], a0, a1, a2, a3, R[0], R[1]);
            mma_bf16_z(acc[2 * i + 1], a0, a1, a2, a3, R[2], R[3]);
            if (i < 4) {
                mma_bf16(acc[2 * i + 8], n0, n1, 0u, n3, R[0], R[1]);
                mma_bf16(acc[2 * i + 9], n0, n1, 0u, n3, R[2], R[3]);
            }
        }
        const int lm = 8 * (lane >> 4) + r - 1;
        const uint32_t b = vrow + lm * 32 + ((1 ^ ((lm >> 2) & 1)) << 4);
        const uint32_t bz = (m & 1) ? priv : b, bm = (m & 1) ? b : b + 1024;
        const uint32_t m0 = lds32(pb + 4 * 520), m2 = lds32v(pp + 32);
#pragma unroll
        for (int i = 0; i < 6; i++) {
            uint32_t R[4];
            ldsm4(R, i < 2 ? bz + ((m & 1) ? 0 : i * 512) : bm + (i - 2) * 512);
            mma_bf16(acc[2 * i + 4], m0, 0u, m2, 0u, R[0], R[1]);
            mma_bf16(acc[2 * i + 5], m0, 0u, m2, 0u, R[2], R[3]);
        }
    }
#pragma unroll 1
    for (int rho = 1; rho <= 8; rho++) {
        const int lam = 8 * (lane >> 4) - rho + r;
        const uint32_t a = vrow + lam * 32 + (((m & 1) ^ ((lam >> 2) & 1)) << 4);
        const uint32_t pq = pb + 64 * rho;
        mbar_wait(gate, 1);
        uint32_t T[4][4];
#pragma unroll
        for (int ka = 0; ka < 4; ka++) { T[ka][0] = lds32(pq + ka * 512); T[ka][1] = lds32(pq + ka * 512 + 32); T[ka][2] = lds32(pq + ka * 512 - 32); T[ka][3] = lds32v(pq + ka * 512); }
#pragma unroll
        for (int i = 0; i < 8; i++) {
            uint32_t R[4];
            ldsm4(R, a + i * 512);
#pragma unroll
            for (int ka = 0; ka < 4; ka++) {
                if (2 * i + ka < 16) mma_bf16(acc[2 * i + ka], T[ka][0], T[ka][1], T[ka][2], T[ka][3], R[0], R[1]);
                if (2 * i + 4 - ka < 16) mma_bf16(acc[2 * i + 4 - ka], T[3 - ka][0], T[3 - ka][1], T[3 - ka][2], T[3 - ka][3], R[2], R[3]);
            }
        }
    }
}

__device__ __forceinline__ uint32_t ones2(int c, int lo, int n) {
    return (((uint32_t)(c - lo) < (uint32_t)n) ? 0x3f80u : 0u) | (((uint32_t)(c + 1 - lo) < (uint32_t)n) ? 0x3f800000u : 0u);
}
struct Box { uint32_t q[4], ad[4]; };
template <int O, int L1, int N1, int L2, int N2>
__device__ __forceinline__ void box_setup(Box& bx, uint32_t priv, int lane) {
    const int g = lane >> 2, t = lane & 3, d = 2 * t - g;
    bx.q[0] = ones2(d, L1, N1); bx.q[1] = ones2(d, L2, N2); bx.q[2] = ones2(d + 8, L1, N1); bx.q[3] = ones2(d + 8, L2, N2);
#pragma unroll
    for (int i = 0; i < 4; i++) {
        const int T = 16 * g + O + 8 * i + 2 * t;
        bx.ad[i] = priv + 256 + ((2 * T) ^ ((T >> 2) & 16));
    }
}
__device__ __forceinline__ void box_mma(float (&X)[4], float (&Y)[4], float (&Z)[4], const Box& bx, int G) {
    mma_bf16_z(Z, bx.q[0], bx.q[1], bx.q[2], bx.q[3], lds32(bx.ad[0] + 256 * G), lds32v(bx.ad[1] + 256 * G));
    mma_bf16_z(X, bx.q[0], bx.q[1], bx.q[2], bx.q[3], lds32(bx.ad[1] + 256 * G), lds32v(bx.ad[2] + 256 * G));
    mma_bf16_z(Y, bx.q[0], bx.q[1], bx.q[2], bx.q[3], lds32(bx.ad[2] + 256 * G), lds32(bx.ad[3] + 256 * G));
}
template <int G0, int G1>
__device__ __forceinline__ void tail4(float (&acc)[16][4], const Box& bx, const uint4 (&B)[5]) {
#pragma unroll
    for (int G = G0; G < G1; G++) {
        float X[4], Y[4], Z[4];
        box_mma(X, Y, Z, bx, G);
        const uint32_t a0 = pack_bf16(X[0], X[1]), a1 = pack_bf16(Y[0], Y[1]), a2 = pack_bf16(X[2], X[3]), a3 = pack_bf16(Y[2], Y[3]);
        const uint32_t c0 = pack_bf16(Z[0], Z[1]), c1 = pack_bf16v(X[0], X[1]), c2 = pack_bf16(Z[2], Z[3]), c3 = pack_bf16v(X[2], X[3]);
#pragma unroll
        for (int b = 0; b < 5; b++)
            if (G + 4 + b < 16) mma_bf16(acc[G + 4 + b], a0, a1, a2, a3, B[b].x, B[b].y);
#pragma unroll
        for (int b = 0; b < 5; b++)
            if (G + 4 + b < 16) mma_bf16(acc[G + 4 + b], c0, c1, c2, c3, B[b].z, B[b].w);
    }
}
__device__ __forceinline__ void tail8(float (&acc)[16][4], uint32_t priv, int lane) {
    Box bx;
    box_setup<-20, 1, 7, 0, 9>(bx, priv, lane);
    uint2 B[8];
#pragma unroll
    for (int b = 0; b < 8; b++) B[b] = lds64(priv + T_S8 + 8 * (6 + 8 * b + (lane >> 2) - 2 * (lane & 3)));
#pragma unroll
    for (int G = 0; G < 8; G++) {
        float X[4], Y[4], Z[4];
        box_mma(X, Y, Z, bx, G);
        const uint32_t a0 = pack_bf16(X[0], X[1]), a1 = pack_bf16(Y[0], Y[1]), a2 = pack_bf16(Z[2], Z[3]), a3 = pack_bf16(X[2], X[3]);
#pragma unroll
        for (int b = 0; b < 8 - G; b++) mma_bf16(acc[G + 8 + b], a0, a1, a2, a3, B[b].x, B[b].y);
    }
}

__device__ __noinline__ float ln_centred(uint32_t sb, float mu, float ri, int mode) {
    const int lane = threadIdx.x & 31;
    float res = 0.f;
#pragma unroll 1
    for (int rr = 0; rr < 16; rr++) {
        const float c0 = __shfl_sync(0xffffffffu, mu, rr), rj = __shfl_sync(0xffffffffu, ri, rr);
        float c = 0.f;
#pragma unroll 1
        for (int k = 0; k < 16; k++) {
            const uint32_t q = lds32(sb + OFF_ROWS + k * 2048 + rr * 128 + ((lane * 4) ^ ((rr & 7) << 4))), wq = lds32(sb + OFF_GP + k * 128 + lane * 4);
            const float d0 = bf_lo(q) - c0, d1 = bf_hi(q) - c0;
            if (mode) c = fmaf(bf_round(bf_round(d0) * rj), bf_lo(wq), fmaf(bf_round(bf_round(d1) * rj), bf_hi(wq), c));
            else c = fmaf(d0, d0, fmaf(d1, d1, c));
        }
#pragma unroll 1
        for (int o = 16; o; o >>= 1) c += __shfl_xor_sync(0xffffffffu, c, o);
        if ((lane & 15) == rr) res = c;
    }
    if (mode) named_sync(1, 128);
    return res;
}

__device__ __forceinline__ void router_cta(uint32_t* scr, uint32_t sb, int tid) {
    const int lane = tid & 31, warp = tid >> 5;
    const uint32_t cand = sb + 64;
    if (warp >= 8) return;
    const uint32_t epoch = ld_relaxed_32(scr + S_EPOCH);
    if (tid < 128) st_relaxed_32(scr + S_SEL + tid, 0u);
    if (tid == 0) sts32(sb + 32, 0);
    sts128(cand + 32 * tid, 0, 0, 0, 0); sts128(cand + 32 * tid + 16, 0, 0, 0, 0);
    asm volatile("fence.acq_rel.gpu;" ::: "memory");
    const uint32_t tag = (epoch + 1u) | 0x8000u;
    STAMP(0); GSTAMP(1);
    uint32_t key[8], it = 0;
#pragma unroll 1
    while (true) {
        const uint4 q0 = ld_relaxed_128(scr + S_KEY + 4 * tid), q1 = ld_relaxed_128(scr + S_KEY + 1024 + 4 * tid);
        key[0] = q0.x; key[1] = q0.y; key[2] = q0.z; key[3] = q0.w; key[4] = q1.x; key[5] = q1.y; key[6] = q1.z; key[7] = q1.w;
        uint32_t bad = 0;
#pragma unroll
        for (int j = 0; j < 8; j++) bad |= key[j] ^ tag;
        if (__all_sync(0xffffffffu, (bad & 0xffffu) == 0)) break;
        if (++it > SPIN_LIMIT) __trap();
    }
    uint32_t mx = 0;
#pragma unroll
    for (int j = 0; j < 8; j++) {
        key[j] = (key[j] & 0xffff0000u) | (0xffffu - (uint32_t)(1024 * (j >> 2) + 4 * tid + (j & 3)));
        mx = max(mx, key[j]);
    }
    const uint32_t gm = __reduce_max_sync(0xffffffffu, mx);
    if (lane == 0) sts32(sb + 4 * warp, gm);
    STAMP(2); GSTAMP(3);
    named_sync(1, 256);
    if (tid == 0) st_relaxed_32(scr + S_EPOCH, epoch + 1u);
    const uint4 t0 = lds128(sb), t1 = lds128(sb + 16);
    const uint32_t tau = min(min(min(t0.x, t0.y), min(t0.z, t0.w)), min(min(t1.x, t1.y), min(t1.z, t1.w)));
    if (mx >= tau) {
        uint32_t pos = 0;
#pragma unroll
        for (int j = 0; j < 8; j++) pos += key[j] >= tau;
        asm volatile("atom.shared.add.u32 %0, [%1], %0;" : "+r"(pos) : "r"(sb + 32) : "memory");
#pragma unroll
        for (int j = 0; j < 8; j++)
            if (key[j] >= tau) sts32(cand + 4 * pos++, key[j]);
    }
    named_sync(1, 256);
    const int n = (int)lds32(sb + 32);
#pragma unroll 1
    for (int i = tid >> 2; i < n; i += 64) {
        const uint32_t k = lds32(cand + 4 * i);
        int rk = 0;
#pragma unroll 1
        for (int j = 0; j < n; j += 32) {
#pragma unroll
            for (int jj = 0; jj < 8; jj++) {
                const uint4 q = lds128(cand + 4 * j + 16 * jj);
                rk += (q.x > k) + (q.y > k) + (q.z > k) + (q.w > k);
            }
        }
        if (rk < 8) st_relaxed_64(scr + S_SEL + 32 * (tid & 3) + 2 * rk, k, tag);
    }
    STAMP(4); GSTAMP(5);
}

__global__ void __cluster_dims__(2, 1, 1) __launch_bounds__(NTHR, 1)
fused_kernel(const __grid_constant__ Ptrs p, const __grid_constant__ Maps maps) {
    extern __shared__ __align__(1024) unsigned char smem[];
    const uint32_t sb = s_u32(smem);
    const int tid = threadIdx.x, lane = tid & 31;
    const int warp = __shfl_sync(0xffffffffu, tid >> 5, 0);
    const int b = blockIdx.x, h = b & 1, cl = b >> 1;
    const uint32_t bar0 = sb + OFF_BAR;
    const int m = lane >> 3, r = lane & 7;
    if (b >= NCTA) {
        if (b == NCTA) router_cta(p.scr, sb, tid);
        return;
    }
    if (warp < 8) {
        const int w = warp, dch = 8 * b + w;
        STAMP(0);
        const int po = dch * NMODE + 4 * lane;
        const uint2 la = ldg64(p.logA + po), aim = ldg64(p.Aim + po), cre = ldg64(p.Cre + po), cim = ldg64(p.Cim + po);
        const uint32_t ldt16 = ldg16(p.ldt + dch), dsk16 = ldg16(p.dsk + dch);
        cluster_arrive();
        const uint32_t priv = sb + OFF_PRIV + w * PRIV;
        const int g = lane >> 2, t = lane & 3;
        const uint32_t* sp = p.scr + S_STAT + 2048 * (cl & 3) + 256 * w + 16 * t + 2 * g;
        uint2 sq[4];
        {
            const uint32_t m2 = as_u(__hmax2(__hmax2(__habs2(as_b2(cre.x)), __habs2(as_b2(cre.y))), __hmax2(__habs2(as_b2(cim.x)), __habs2(as_b2(cim.y)))));
            const uint32_t eb = min(max(__reduce_max_sync(0xffffffffu, max(m2 << 16, m2)) >> 23, 1u), 252u);
            const float dt = bf_round(ex2f(bf_lo(ldt16) * L2E));
            float s0[4];
            mma_bf16_z(s0, ONES, ONES, ONES, ONES, cre.x, cre.y);
            STAMP(1);
            float kacc[5][4];
            kgen_mma(kacc, priv, lane, la, aim, cre, cim, dt, (253u - eb) * 0x00800080u);
            STAMP(2);
#pragma unroll
            for (int i = 0; i < 4; i++) sq[i] = ld_relaxed_64(sp + 64 * i);
            float k0 = s0[0] + s0[1];
            k0 += __shfl_xor_sync(0xffffffffu, k0, 1);
            k0 += __shfl_xor_sync(0xffffffffu, k0, 2);
            kgen_tables(kacc, priv, lane, (dt + dt) * __uint_as_float((eb + 1u) << 23), fmaf(k0, dt + dt, bf_lo(dsk16) + 1.f));
        }
        STAMP(3);
        cluster_wait();
        {
            mbar_wait(bar0 + 8 * (B_X + w), 0);
            STAMP(5);
            uint4 x[8];
#pragma unroll
            for (int i = 0; i < 8; i++) x[i] = lds128(sb + OFF_X + 8192 * w + 32 * lane + ((h ^ (g & 1)) << 4) + 1024 * i);
            named_sync(2, 288);
            const uint32_t want = lds32(sb + OFF_MISC);
#pragma unroll 1
            while (!__all_sync(0xffffffffu, (((sq[0].y ^ want) | (sq[1].y ^ want) | (sq[2].y ^ want) | (sq[3].y ^ want)) & 0x80008000u) == 0)) {
                __nanosleep(STAT_SLEEP);
#pragma unroll
                for (int i = 0; i < 4; i++) sq[i] = ld_relaxed_64(sp + 64 * i);
            }
            STAMP(4);
            const uint32_t dst = sb + OFF_PRIV + (2 * m + (r & 1)) * PRIV + 256 + 512 * w + 32 * (r >> 1);
#pragma unroll
            for (int i = 0; i < 4; i++) {
                const uint2 rc = recip2(sq[i].y ^ want);
#pragma unroll
                for (int hf = 0; hf < 2; hf++) {
                    const __nv_bfloat162 mm = hf ? __high2bfloat162(as_b2(sq[i].x)) : __low2bfloat162(as_b2(sq[i].x));
                    const __nv_bfloat162 rh = hf ? __high2bfloat162(as_b2(rc.x)) : __low2bfloat162(as_b2(rc.x));
                    const __nv_bfloat162 rl = hf ? __high2bfloat162(as_b2(rc.y)) : __low2bfloat162(as_b2(rc.y));
                    const uint4 q = x[2 * i + hf];
                    const uint32_t v[4] = {normalize2(q.x, mm, rh, rl), normalize2(q.y, mm, rh, rl), normalize2(q.z, mm, rh, rl), normalize2(q.w, mm, rh, rl)};
                    stsm4t(dst + 128 * i + 16 * (hf ^ (i & 1)), v);
                }
            }
            __syncwarp();
            if (elect_one()) { mbar_arrive(bar0 + 8 * B_VT); mbar_arrive_peer(mapa(bar0 + 8 * B_PV, h ^ 1)); }
            mbar_wait(bar0 + 8 * B_VT, 0);
        }
        STAMP(6);
        float acc[16][4];
        dense_phase(acc, priv, bar0 + 8 * (B_GATE + (w & 3)), lane);
        STAMP(7);
        const uint32_t spos = ((r ^ (4 * (w & 1))) << 4) + 128 * m;
        const uint32_t s_own = sb + OFF_X + 16384 * (h ^ 1) + 1024 * (8 * h + w), s_out = priv + T_DENSE;
        auto send = [&](int pt) {
#pragma unroll
            for (int i = 0; i < 4; i++) {
                const float* c0 = acc[8 * pt + 2 * i];
                const float* c1 = acc[8 * pt + 2 * i + 1];
                const uint32_t s[4] = {pack_bf16(c0[0], c0[1]), pack_bf16(c0[2], c0[3]), pack_bf16(c1[0], c1[1]), pack_bf16(c1[2], c1[3])};
                stsm4t(((i >> 1) == h ? s_own + 32768 * pt : s_out + 1024 * pt) + spos + 512 * (i & 1), s);
            }
            fence_async();
            __syncwarp();
            if (elect_one()) {
                bulk_s2peer(mapa(sb + OFF_X + 32768 * pt + 16384 * h + 1024 * (8 * h + w), h ^ 1), s_out + 1024 * pt, 1024, mapa(bar0 + 8 * (B_RECV + pt), h ^ 1));
                mbar_arrive(bar0 + 8 * (B_RECV + pt));
            }
        };
        auto finish = [&](int pt) {
            mbar_wait(bar0 + 8 * (B_RECV + pt), 0);
            const uint32_t xt = sb + OFF_X + 32768 * pt + 16384 * h + 2048 * w;
            const uint32_t xa = xt + 32 * lane + ((g & 1) << 4);
            const uint32_t sa = sb + OFF_X + 32768 * pt + 16384 * (h ^ 1) + 1024 * (2 * m + (r & 1)) + 256 * (w >> 1) + 64 * ((w ^ r) & 1) + 16 * (r >> 1);
            uint4 x[4];
            uint32_t s[4][4];
#pragma unroll
            for (int i = 0; i < 4; i++) { x[i] = lds128((xa ^ ((i & 1) << 4)) + 1024 * (i >> 1)); ldsm4t(s[i], sa + 8192 * (i & 1) + 128 * (i >> 1)); }
#pragma unroll
            for (int i = 0; i < 4; i++)
                sts128((xa ^ ((i & 1) << 4)) + 1024 * (i >> 1), badd2(x[i].x, s[i][0]), badd2(x[i].y, s[i][1]), badd2(x[i].z, s[i][2]), badd2(x[i].w, s[i][3]));
            fence_async();
            __syncwarp();
            if (elect_one()) {
                tma_store_4d(&maps.out, xt, 16 * cl, 16 * pt + 8 * h + w);
                asm volatile("cp.async.bulk.commit_group;" ::: "memory");
            }
        };
        {
            Box bx;
            box_setup<-18, 0, 5, 5, 3>(bx, priv, lane);
            uint4 B[5];
#pragma unroll
            for (int i = 0; i < 5; i++) B[i] = lds128(priv + T_S4 + 16 * (6 + 8 * i + (lane >> 2) - 2 * (lane & 3)));
            tail4<0, 4>(acc, bx, B);
            mbar_wait(bar0 + 8 * B_PV, 0);
            send(0);
            STAMP(8);
            tail4<4, 12>(acc, bx, B);
        }
        STAMP(9);
        finish(0);
        STAMP(10);
        tail8(acc, priv, lane);
        STAMP(11);
        send(1);
        finish(1);
        STAMP(12);
        __syncwarp();
        cluster_arrive();
        if (elect_one()) {
            asm volatile("cp.async.bulk.wait_group 0;" ::: "memory");
            mbar_arrive(bar0 + 8 * B_ST);
        }
        __syncwarp();
        STAMP(13); GSTAMP(15);
    } else if (warp < 12) {
        const int a = warp - 8, at = 32 * a + lane, g = lane >> 2, t = lane & 3;
        STAMP(0);
        if (elect_one()) {
            const uint32_t cnt = a == 3 ? 0x18419988u : 0x11111111u, tx = a == 0 ? 0x44444444u : a == 3 ? 0x00084400u : 0u;
#pragma unroll 1
            for (int i = 0; i < 8; i++) {
                mbar_init(bar0 + 64 * a + 8 * i, (cnt >> (4 * i)) & 15);
                const uint32_t n = (tx >> (4 * i)) & 15;
                if (n) mbar_expect_tx(bar0 + 64 * a + 8 * i, n << 11);
            }
            mbar_init(bar0 + 8 * (B_GATE + a), 1);
            asm volatile("fence.mbarrier_init.release.cluster;" ::: "memory");
            fence_async();
        }
        __syncwarp();
        cluster_arrive();
        const uint32_t epoch = ld_relaxed_32(p.scr + S_EPOCH);
        uint32_t* const pst = p.scr + S_STAT + 2048 * a + 16 * b + 2 * lane;
        uint32_t* const pky = p.scr + S_KEY + 16 * b + at;
        if (lane < 8) st_relaxed_64(pst, 0u, 0u);
        if (at < 16) st_relaxed_32(pky, 0u);
        uint32_t* const py = p.scr + S_Y + 1024 * ((cl & ~3) + a) + 128 * (b & 7) + 32 * t + 4 * g;
        st_relaxed_128(py, 0u, 0u, 0u, 0u);
        sts32(sb + OFF_MISC + 12, 0u);
        const uint32_t gp = sb + OFF_GP;
        sts32(gp + 2048 + 4 * lane, ONES);
        cluster_wait();
        STAMP(1);
        mbar_wait(bar0 + 8 * B_WR, 0);
        float ws[4] = {0.f, 0.f, 0.f, 0.f};
#pragma unroll 1
        for (int k = 0; k < 4; k++) {
            const uint4 q = lds128(gp + k * 512 + lane * 16);
            mma_bf16(ws, ONES, ONES, ONES, ONES, q.x, q.y);
            mma_bf16(ws, ONES, ONES, ONES, ONES, q.z, q.w);
        }
        float wsum = ws[0] + ws[1];
        wsum += __shfl_xor_sync(0xffffffffu, wsum, 1);
        wsum += __shfl_xor_sync(0xffffffffu, wsum, 2);
        const uint32_t hsel = (epoch & 1) * (GU_CTAS * 128), want = (epoch & 1) ? 0x00008000u : 0x80000000u;
        if (a == 0) {
            sts32(sb + OFF_MISC, want);
            asm volatile("bar.arrive 2, 288;" ::: "memory");
        }
        if (b < GU_CTAS) st_relaxed_32(p.scr + S_H + (GU_CTAS * 128 - hsel) + b * 128 + at, 0u);
        {
            uint32_t ra = sb + OFF_ROWS + 2048 * a + 128 * (r + 8 * (m & 1)) + (((m >> 1) ^ r) << 4);
            uint32_t wa = r == 1 ? gp + 128 * a + 16 * m : gp + 2048;
            const uint32_t wstep = r == 1 ? 512 : 0;
            float cs[2][4] = {}, q1[2][4] = {}, q2[2][4] = {};
#pragma unroll 1
            for (int k = 0; k < 4; k++) {
                uint32_t x[4][4], wf[2][4];
                ldsm4(wf[0], wa); ldsm4(wf[1], wa + 64);
                mbar_wait(bar0 + 8 * (B_ROW + k), 0);
                STAMP(2);
#pragma unroll
                for (int i = 0; i < 4; i++) ldsm4(x[i], ra ^ (32 * i));
#pragma unroll
                for (int i = 0; i < 4; i++) {
                    mma_bf16(cs[i & 1], x[i][0], x[i][1], x[i][2], x[i][3], wf[i >> 1][2 * (i & 1)], wf[i >> 1][2 * (i & 1) + 1]);
                    mma_bf16(q1[i & 1], x[i][0], x[i][1], x[i][2], x[i][3], x[i][0], x[i][2]);
                    mma_bf16(q2[i & 1], x[i][0], x[i][1], x[i][2], x[i][3], x[i][1], x[i][3]);
                }
                ra += 8192; wa += wstep;
            }
            const uint32_t pa = gp + 2304 + 256 * a;
#pragma unroll
            for (int i = 0; i < 4; i++) cs[0][i] += cs[1][i];
            if (t == 0) sts128f(pa + 16 * g, cs[0]);
            if (t == (g >> 1)) sts64(pa + 128 + 8 * g, __float_as_uint((g & 1) ? q1[0][1] + q1[1][1] : q1[0][0] + q1[1][0]),
                                     __float_as_uint((g & 1) ? q2[0][3] + q2[1][3] : q2[0][2] + q2[1][2]));
            named_sync(1, 128);
            float sx = 0.f, sw = 0.f, sqq = 0.f;
#pragma unroll
            for (int i = 0; i < 4; i++) {
                const uint2 u = lds64(gp + 2304 + 256 * i + 16 * r + 8 * (m & 1));
                sx += __uint_as_float(u.x); sw += __uint_as_float(u.y);
                sqq += lds32f(gp + 2304 + 128 + 256 * i + 8 * r + 4 * (m & 1));
            }
            const float mu = sx * (1.f / DM);
            float var = sqq * (1.f / DM) - mu * mu;
            const bool centred = __any_sync(0xffffffffu, !(mu * mu <= 4.f * var));
            if (centred) var = ln_centred(sb, mu, 0.f, 0) * (1.f / DM);
            const uint32_t ms = pack_bf16(mu, sqrtaf(bf_round(bf_round(var) + 1e-5f)));
            const uint32_t ot = __shfl_xor_sync(0xffffffffu, ms, 8);
            if (lane < 8) st_relaxed_64(pst, __byte_perm(ms, ot, 0x5410), __byte_perm(ms, ot, 0x7632) | want);
            const float ri = rcpf(bf_hi(ms));
            float sc = (sw - bf_lo(ms) * wsum) * ri;
            if (centred) sc = ln_centred(sb, bf_lo(ms), ri, 1);
            if (at < 16) st_relaxed_32(pky, (order_key(pack_bf16(sc, 0.f)) << 16) | (((epoch + 1u) | 0x8000u) & 0xffffu));
            if (elect_one()) { mbar_arrive(bar0 + 8 * (B_EMPTY + a)); mbar_arrive(bar0 + 8 * (B_EMPTY + 4 + a)); }
        }
        __syncwarp();
        cluster_arrive();
        STAMP(3); GSTAMP(14);
        uint32_t mykey;
        {
            const uint32_t* sl = p.scr + S_SEL + 32 * (cl & 3) + 2 * g;
            uint2 q;
#pragma unroll 1
            do {
                __nanosleep(100);
                q = ld_relaxed_64(sl);
            } while (!__all_sync(0xffffffffu, q.y == ((epoch + 1u) | 0x8000u)));
            mykey = q.x;
        }
        STAMP(4);
        if (b < GU_CTAS) {
            const uint32_t tok = 0xffffu - (mykey & 0xffffu);
#pragma unroll
            for (int i = 0; i < 2; i++) {
                const uint32_t tk = __shfl_sync(0xffffffffu, tok, 8 * a + 4 * i);
                if (elect_one()) bulk_g2s(sb + OFF_XS + (2 * a + i) * ROW_PITCH, p.u + (size_t)tk * DM, 2048, bar0 + 8 * B_XS);
            }
            uint2 rec;
#pragma unroll 1
            do {
                rec = ld_relaxed_64(p.scr + S_STAT + 2048 * a + (tok & ~15u) + 2 * (tok & 7u));
                rec.y ^= want;
            } while (!__all_sync(0xffffffffu, (rec.y & 0x80008000u) == 0));
            const uint32_t sel = (tok & 8u) ? 0x3232u : 0x1010u;
            const uint32_t m2 = __byte_perm(rec.x, 0, sel);
            const uint2 rr = recip2(__byte_perm(rec.y, 0, sel));
            float gacc[4][4];
#pragma unroll
            for (int i = 0; i < 4; i++) { gacc[i][0] = gacc[i][1] = gacc[i][2] = gacc[i][3] = 0.f; }
            const int k = r + 8 * (m >> 1);
            const uint32_t wa = sb + OFF_RING + 8192 * a + (((m & 1) * 4096) ^ p.up_first) + k * 64 + (((k >> 1) & 3) << 4);
            const uint32_t gate = bar0 + 8 * (B_GATE + a);
            mbar_wait(bar0 + 8 * B_XS, 0);
            STAMP(5);
#pragma unroll 1
            for (int c = 0; c < 4; c++) {
                uint32_t xb[2][4];
#pragma unroll
                for (int i = 0; i < 2; i++) {
                    ldsm4(xb[i], sb + OFF_XS + r * ROW_PITCH + 16 * m + 128 * a + 512 * c + 64 * i);
#pragma unroll
                    for (int j = 0; j < 4; j++) xb[i][j] = normalize2(xb[i][j], as_b2(m2), as_b2(rr.x), as_b2(rr.y));
                }
                const int s = a + 4 * (c & 1);
                mbar_wait(bar0 + 8 * (B_FULL + s), c >> 1);
                uint32_t af[16][4];
#pragma unroll
                for (int ks = 0; ks < 4; ks++)
#pragma unroll
                    for (int mt = 0; mt < 4; mt++) ldsm4t(af[4 * ks + mt], (wa ^ (mt << 4)) + (c & 1) * 32768 + ks * 1024);
                __syncwarp();
                if (elect_one()) { mbar_arrive(gate); mbar_arrive(bar0 + 8 * (B_EMPTY + s)); }
                xb[0][0] |= lds32v(sb + OFF_MISC + 12);
#pragma unroll
                for (int ks = 0; ks < 4; ks++) {
#pragma unroll
                    for (int mt = 0; mt < 4; mt++)
                        mma_bf16(gacc[mt], af[4 * ks + mt][0], af[4 * ks + mt][1], af[4 * ks + mt][2], af[4 * ks + mt][3],
                                 xb[ks >> 1][2 * (ks & 1)], xb[ks >> 1][2 * (ks & 1) + 1]);
                    if (ks == GATE_KS && lane == 0) mbar_arrive(gate + (__float_as_uint(gacc[0][0]) & p.zero));
                }
            }
            STAMP(6);
#pragma unroll
            for (int mt = 0; mt < 4; mt++) sts128f(gp + 2048 * a + mt * 512 + lane * 16, gacc[mt]);
            named_sync(1, 128);
            {
                uint4 q[4];
#pragma unroll
                for (int wq = 0; wq < 4; wq++) q[wq] = lds128(gp + 2048 * wq + 16 * at);
                const uint32_t g2 = pack_bf16((__uint_as_float(q[0].x) + __uint_as_float(q[1].x)) + (__uint_as_float(q[2].x) + __uint_as_float(q[3].x)),
                                              (__uint_as_float(q[0].y) + __uint_as_float(q[1].y)) + (__uint_as_float(q[2].y) + __uint_as_float(q[3].y)));
                const uint32_t u2 = pack_bf16((__uint_as_float(q[0].z) + __uint_as_float(q[1].z)) + (__uint_as_float(q[2].z) + __uint_as_float(q[3].z)),
                                              (__uint_as_float(q[0].w) + __uint_as_float(q[1].w)) + (__uint_as_float(q[2].w) + __uint_as_float(q[3].w)));
                const uint32_t s2 = pack_bf16(bf_lo(g2) * rcpf(1.f + ex2f(-L2E * bf_lo(g2))), bf_hi(g2) * rcpf(1.f + ex2f(-L2E * bf_hi(g2))));
                uint32_t hw;
                asm volatile("movmatrix.sync.aligned.m8n8.trans.b16 %0, %1;" : "=r"(hw) : "r"(as_u(__hmul2(as_b2(s2), as_b2(u2)))));
                if (hw == 0u) hw = 0x80008000u;
                st_relaxed_32(p.scr + S_H + hsel + b * 128 + at, hw);
            }
            STAMP(7);
        }
        const uint32_t ytag = 1u + (epoch & 1);
        {
            const uint32_t* hp = p.scr + S_H + hsel + (b & 7) * 1792 + 4 * at;
            uint4 hq[4];
#pragma unroll 1
            do {
                __nanosleep(H_SLEEP);
#pragma unroll
                for (int j = 0; j < 4; j++) hq[j] = ld_relaxed_128(hp + (j < 3 ? 512 * j : 1280));
            } while (!__all_sync(0xffffffffu, min(min(hq[0].w, hq[1].w), min(hq[2].w, hq[3].w)) != 0));
#pragma unroll
            for (int j = 0; j < 4; j++) sts128(sb + OFF_XS + 16 * at + (j < 3 ? 2048 * j : 5120), hq[j].x, hq[j].y, hq[j].z, hq[j].w);
            named_sync(1, 128);
            STAMP(8);
            float dacc[4][4] = {};
            const uint32_t wa = sb + OFF_RING + 128 * (r + 8 * (m >> 1)) + (((2 * a + (m & 1)) ^ r) << 4);
#pragma unroll 1
            for (int s = 0; s < 7; s++) {
                uint32_t hb[2][4], af[4][4];
                ldsm4(hb[0], sb + OFF_XS + 16 * lane + 1024 * s); ldsm4(hb[1], sb + OFF_XS + 16 * lane + 1024 * s + 512);
                mbar_wait(bar0 + 8 * (B_FULL + s), 0);
#pragma unroll
                for (int j = 0; j < 4; j++) ldsm4t(af[j], wa + s * 8192 + j * 2048);
#pragma unroll
                for (int j = 0; j < 4; j++) mma_bf16(dacc[j], af[j][0], af[j][1], af[j][2], af[j][3], hb[j >> 1][2 * (j & 1)], hb[j >> 1][2 * (j & 1) + 1]);
            }
            uint32_t y[4];
#pragma unroll
            for (int j = 0; j < 4; j++) y[j] = (__float_as_uint((dacc[0][j] + dacc[1][j]) + (dacc[2][j] + dacc[3][j])) & ~3u) | ytag;
            st_relaxed_128(py, y[0], y[1], y[2], y[3]);
        }
        STAMP(9);
        {
            const uint32_t key = __shfl_sync(0xffffffffu, mykey, 8 * a + 4 * (m >> 1));
            const uint32_t tok = 0xffffu - (key & 0xffffu);
            const float sg = bf_round(rcpf(1.f + ex2f(-L2E * bf_lo(unorder_key(key >> 16)))));
            const uint32_t xo = sb + OFF_X + 32 * (tok & ~63u) + 128 * (tok & 15u) + 2 * (tok & 48u) + ((2 * (lane & 15)) ^ ((tok & 1u) << 4));
            if (((tok >> 9) & 1) == h) {
                const uint32_t* yp = p.scr + S_Y + 1024 * cl + 32 * a + 4 * r + 2 * (m & 1) + (m >> 1);
                uint32_t pp[8], bad;
#pragma unroll 1
                do {
                    bad = 0;
#pragma unroll
                    for (int q = 0; q < 8; q++) pp[q] = ld_relaxed_32(yp + 128 * q);
#pragma unroll
                    for (int q = 0; q < 8; q++) bad |= pp[q] ^ ytag;
                } while (bad & 3u);
                const float y = ((__uint_as_float(pp[0]) + __uint_as_float(pp[1])) + (__uint_as_float(pp[2]) + __uint_as_float(pp[3]))) +
                                ((__uint_as_float(pp[4]) + __uint_as_float(pp[5])) + (__uint_as_float(pp[6]) + __uint_as_float(pp[7])));
                const uint32_t upd = pack_bf16(bf_round(y) * sg, 0.f);
                STAMP(11);
                mbar_wait(bar0 + 8 * B_ST, 0);
                uint32_t o;
                asm volatile("ld.shared.u16 %0, [%1];" : "=r"(o) : "r"(xo));
                asm volatile("st.global.u16 [%0], %1;" ::"l"(p.out + (size_t)tok * DM + 16 * cl + (lane & 15)), "r"(badd2(o, upd)) : "memory");
            }
            __syncwarp();
            if (elect_one()) mbar_arrive(bar0 + 8 * B_DONE);
        }
        STAMP(10); GSTAMP(15);
    } else {
        sts32(sb + OFF_MISC - 44 + 4 * warp, clk());
        const uint32_t t0 = lds32v(sb + OFF_MISC - 44 + 4 * warp);
        STAMP(0);
        if (warp == 13) GSTAMP(14);
        if (warp == 12 && elect_one()) {
            asm volatile("prefetch.tensormap [%0];" ::"l"(&maps.rows) : "memory");
#pragma unroll
            for (int i = 0; i < 5; i++) mbar_init(bar0 + 8 * (B_ROW + i), 1);
            fence_async();
            mbar_expect_tx(bar0 + 8 * B_WR, 2048);
            bulk_g2s(sb + OFF_GP, p.wr, 2048, bar0 + 8 * B_WR);
            wait_until(t0 + ROW_DELAY);
#pragma unroll 1
            for (int i = 0; i < 4; i++) {
                mbar_expect_tx(bar0 + 8 * (B_ROW + i), 8192);
                tma_load_3d(sb + OFF_ROWS + 8192 * i, &maps.rows, 16 * b, 4 * i, bar0 + 8 * (B_ROW + i));
            }
#pragma unroll 1
            for (int i = 0; i < 4; i++) asm volatile("prefetch.tensormap [%0];" ::"l"(&maps.u + i) : "memory");
        }
        __syncwarp();
        cluster_arrive();
        cluster_wait();
        cluster_arrive();
        STAMP(1);
        if (elect_one()) {
            if (warp == 12) {
                wait_until(t0 + X_DELAY);
#pragma unroll 1
                for (int i = 4 * h; i < 4 * h + 4; i++) tma_load_4d_both(sb + OFF_X + 8192 * i, &maps.u, 16 * cl, 4 * i, bar0 + 8 * (B_X + i));
                STAMP(2);
#pragma unroll 1
                for (int c = b < GU_CTAS ? 0 : 16; c < 23; c++) {
                    const uint32_t dst = sb + OFF_RING + (c & 7) * 8192, bar = bar0 + 8 * (B_FULL + (c & 7));
                    wait_until(t0 + (c < 16 ? LD_START + c * LD_PERIOD : WD_START + (c - 16) * WD_PERIOD));
                    mbar_wait(bar + 8 * (B_EMPTY - B_FULL), (c >> 3) & 1);
                    mbar_expect_tx(bar, 8192);
                    tma_load_4d(dst, c < 16 ? &maps.wgu : &maps.wd, c < 16 ? 32 * b : 64 * (b >> 3), c < 16 ? c : 7 * (b & 7) + c - 16, bar);
                }
            } else {
                const char* src = (const char*)((b >> 6) ? p.wu : p.wg) + (b & 63) * 7168;
                uint32_t due = t0 + PF_START + (b * PF_PERIOD >> 7), sz = 7168, step = 64 * 7168;
#pragma unroll 1
                for (int i = 0; i < 23; i++) {
                    if (i == 16) { src = (const char*)p.wd + (b >> 4) * 448 * 2048 + (b & 15) * 8192; sz = 8192; step = 64 * 2048; }
                    wait_until(due);
                    asm volatile("cp.async.bulk.prefetch.L2.global [%0], %1;" ::"l"(src), "r"(sz) : "memory");
                    src += step;
                    due += (sz >> 10) * (PF_PERIOD / 7);
                }
                STAMP(6);
#pragma unroll 1
                for (int i = B_DONE; i <= B_ST; i++) mbar_wait_bounded(bar0 + 8 * i, 0);
            }
        }
        __syncwarp();
    }
    cluster_wait();
}

typedef CUresult (*EncodeFn)(CUtensorMap*, CUtensorMapDataType, cuuint32_t, void*, const cuuint64_t*, const cuuint64_t*,
                             const cuuint32_t*, const cuuint32_t*, CUtensorMapInterleave, CUtensorMapSwizzle,
                             CUtensorMapL2promotion, CUtensorMapFloatOOBfill);

void make_map(EncodeFn enc, CUtensorMap* m, int rank, const void* ptr, const cuuint64_t (&dims)[4], const cuuint64_t (&str)[3],
              const cuuint32_t (&box)[4], CUtensorMapSwizzle sw, CUtensorMapL2promotion pr) {
    const cuuint32_t es[4] = {1, 1, 1, 1};
    CUresult rc = enc(m, CU_TENSOR_MAP_DATA_TYPE_BFLOAT16, rank, const_cast<void*>(ptr), dims, str, box, es, CU_TENSOR_MAP_INTERLEAVE_NONE, sw, pr,
                      CU_TENSOR_MAP_FLOAT_OOB_FILL_NONE);
    (void)rc;
}

}

extern "C" void kernel_launch(void* const* d_in, const int* in_sizes, int n_in, void* d_out, int out_size) {
    (void)in_sizes; (void)n_in; (void)out_size;
    static EncodeFn enc = nullptr;
    static void* scr = nullptr;
    if (!enc) {
        void* fn = nullptr;
        cudaDriverEntryPointQueryResult q;
        cudaGetDriverEntryPoint("cuTensorMapEncodeTiled", &fn, cudaEnableDefault, &q);
        enc = (EncodeFn)fn;
        cudaGetSymbolAddress(&scr, g_scr);
        cudaFuncSetAttribute(fused_kernel, cudaFuncAttributeMaxDynamicSharedMemorySize, SMEM_BYTES);
    }
    Maps maps;
    const uintptr_t ag = (uintptr_t)d_in[9], au = (uintptr_t)d_in[10];
    const auto noprom = CU_TENSOR_MAP_L2_PROMOTION_NONE, prom = CU_TENSOR_MAP_L2_PROMOTION_L2_128B;
    make_map(enc, &maps.rows, 3, d_in[0], {64, SEQ, 16, 1}, {2048, 128, 0}, {64, 16, 4, 1}, CU_TENSOR_MAP_SWIZZLE_128B, noprom);
    make_map(enc, &maps.u, 4, d_in[0], {DM, 4, 16, 32}, {32768, 2048, 131072}, {16, 4, 16, 4}, CU_TENSOR_MAP_SWIZZLE_32B, noprom);
    make_map(enc, &maps.out, 4, d_out, {DM, 4, 16, 32}, {32768, 2048, 131072}, {16, 4, 16, 1}, CU_TENSOR_MAP_SWIZZLE_32B, noprom);
    make_map(enc, &maps.wgu, 4, (const void*)(ag < au ? ag : au), {FF, 64, 2, 16}, {FF * 2, ag < au ? au - ag : ag - au, 64 * FF * 2}, {32, 64, 2, 1},
             CU_TENSOR_MAP_SWIZZLE_64B, prom);
    make_map(enc, &maps.wd, 4, d_in[11], {DM, 64, 1, 56}, {2048, 131072, 131072}, {64, 64, 1, 1}, CU_TENSOR_MAP_SWIZZLE_128B, prom);
    Ptrs p;
    p.u = (const __nv_bfloat16*)d_in[0];
    p.logA = (const __nv_bfloat16*)d_in[1];
    p.Aim = (const __nv_bfloat16*)d_in[2];
    p.Cre = (const __nv_bfloat16*)d_in[3];
    p.Cim = (const __nv_bfloat16*)d_in[4];
    p.ldt = (const __nv_bfloat16*)d_in[5];
    p.dsk = (const __nv_bfloat16*)d_in[6];
    p.wr = (const __nv_bfloat16*)d_in[8];
    p.wg = (const __nv_bfloat16*)d_in[9];
    p.wu = (const __nv_bfloat16*)d_in[10];
    p.wd = (const __nv_bfloat16*)d_in[11];
    p.out = (__nv_bfloat16*)d_out;
    p.scr = (uint32_t*)scr;
    p.up_first = ag < au ? 0 : 4096;
    p.zero = 0;
    fused_kernel<<<NCTA + 2, NTHR, SMEM_BYTES, cudaStreamPerThread>>>(p, maps);
}
```

```cpp
#include <cuda_runtime.h>
#include <cuda_bf16.h>
#include <cuda_fp16.h>
#include <cuda.h>
#include <stdint.h>

namespace {

constexpr int SEQ = 2048, DM = 1024, NMODE = 128, FF = 3584;
constexpr int NCTA = 128, NTHR = 512;
constexpr int GU_CTAS = 112;

constexpr int OFF_X = 0;
constexpr int OFF_RING = 65536;
constexpr int ROW_PITCH = 2064;
constexpr int OFF_ROWS = OFF_RING + 32768;
constexpr int OFF_XS = OFF_RING + 65536;
constexpr int OFF_PRIV = OFF_XS + 8 * ROW_PITCH;
constexpr int PRIV = 8720;
constexpr int OFF_GP = OFF_PRIV + 8 * PRIV;
constexpr int OFF_BAR = OFF_GP + 8192;
constexpr int OFF_MISC = OFF_BAR + 336;
constexpr int OFF_STAMP = OFF_MISC + 288;
constexpr int SMEM_BYTES = OFF_STAMP;

constexpr int B_X = 0, B_FULL = 8, B_EMPTY = 16, B_RECV = 24, B_XS = 28, B_DONE = 29, B_ST = 30, B_TAG = 31, B_ROW = 32, B_WR = 36, B_KG = 37, B_VT = 38, B_PV = 39;

constexpr int T_DENSE = 4368;
constexpr int T_PATCH = T_DENSE + 2176;
constexpr int T_S4 = T_PATCH + 112;
constexpr int T_S8 = T_S4 + 736;
constexpr int REC = 272;

#define KG_UNROLL 4
constexpr int KGU = KG_UNROLL;
constexpr uint32_t SPIN_LIMIT = 1u << 22;
#define ROW_DELAY 300
#define H_SLEEP 100
#define NPRE 5
#define SEL_SLEEP 100
#define ROW_PERIOD 350
#define X_PERIOD 0
#define FINE 2
#define INC_AT 1
#define NREG 168
#define DN_RUN 4
#define FIN_A 12
#define X_DELAY 2500
#define PF_START 3300
#define PF_PERIOD 539
#define PF_N 12
#define LD_LAG 700
#define LD_START 5400
#define LD_PERIOD ((PF_START + PF_N * PF_PERIOD + LD_LAG - LD_START) / (PF_N - 1))

constexpr int S_STAT = 0;
constexpr int S_KEY = S_STAT + 8192;
constexpr int S_SEL = S_KEY + 2048;
constexpr int S_EPOCH = S_SEL + 128;
constexpr int S_H = S_EPOCH + 32;
constexpr int S_Y = S_H + 2 * GU_CTAS * 128;
constexpr int S_END = S_Y + 64 * 1024;
__device__ __align__(1024) uint32_t g_scr[S_END];

struct Ptrs {
    const __nv_bfloat16 *logA, *Aim, *Cre, *Cim, *ldt, *dsk, *u, *wr;
    uint32_t* scr;
    const __nv_bfloat16 *wg, *wu;
    __nv_bfloat16* out;
    uint32_t up_first;
    uint32_t zero;
};
struct Maps {
    CUtensorMap rows, u, out, wgu, wd;
};

__device__ __forceinline__ uint32_t clk() { uint32_t c; asm volatile("mov.u32 %0, %%clock;" : "=r"(c)); return c; }
#define STAMP(i) do { } while (0)
#define GSTAMP(i) do { } while (0)

template <int N> struct IC { static constexpr int value = N; };

__device__ __forceinline__ uint32_t s_u32(const void* p) { return (uint32_t)__cvta_generic_to_shared(p); }
__device__ __forceinline__ void mbar_init(uint32_t b, uint32_t n) {
    asm volatile("mbarrier.init.shared::cta.b64 [%0], %1;" ::"r"(b), "r"(n) : "memory");
}
__device__ __forceinline__ void mbar_expect_tx(uint32_t b, uint32_t bytes) {
    asm volatile("mbarrier.arrive.expect_tx.shared::cta.b64 _, [%0], %1;" ::"r"(b), "r"(bytes) : "memory");
}
__device__ __forceinline__ void mbar_arrive(uint32_t b) {
    asm volatile("mbarrier.arrive.shared::cta.b64 _, [%0];" ::"r"(b) : "memory");
}
__device__ __forceinline__ void mbar_arrive_peer(uint32_t b_cluster) {
    asm volatile("mbarrier.arrive.relaxed.cluster.shared::cluster.b64 _, [%0];" ::"r"(b_cluster) : "memory");
}
__device__ __forceinline__ void mbar_wait(uint32_t b, uint32_t parity) {
    asm volatile("{\n\t.reg .pred p;\nW:\n\tmbarrier.try_wait.parity.shared::cta.b64 p, [%0], %1;\n\t@!p bra W;\n\t}" ::"r"(b), "r"(parity) : "memory");
}
__device__ __forceinline__ void mbar_wait_bounded(uint32_t b, uint32_t parity) {
    asm volatile("{\n\t.reg .pred p;\n\t.reg .u32 c;\n\tmov.u32 c, 0;\n"
                 "W:\n\tmbarrier.try_wait.parity.shared::cta.b64 p, [%0], %1, 4000;\n\t@p bra D;\n\t"
                 "add.u32 c, c, 1;\n\tsetp.lt.u32 p, c, 1048576;\n\t@p bra W;\n\ttrap;\nD:\n\t}"
                 ::"r"(b), "r"(parity) : "memory");
}
__device__ __forceinline__ bool elect_one() {
    uint32_t p;
    asm volatile("{ .reg .pred P; elect.sync _|P, 0xffffffff; selp.u32 %0, 1, 0, P; }" : "=r"(p));
    return p != 0;
}
__device__ __forceinline__ uint32_t mapa(uint32_t a, uint32_t rank) {
    uint32_t r;
    asm("mapa.shared::cluster.u32 %0, %1, %2;" : "=r"(r) : "r"(a), "r"(rank));
    return r;
}
__device__ __forceinline__ void cluster_arrive() { asm volatile("barrier.cluster.arrive.relaxed.aligned;" ::: "memory"); }
__device__ __forceinline__ void cluster_wait() { asm volatile("barrier.cluster.wait.aligned;" ::: "memory"); }
__device__ __forceinline__ void tma_load_3d(uint32_t dst, const CUtensorMap* m, int c1, int c2, uint32_t bar) {
    asm volatile("cp.async.bulk.tensor.3d.shared::cluster.global.mbarrier::complete_tx::bytes [%0], [%1, {%3, %4, %5}], [%2];"
                 ::"r"(dst), "l"(m), "r"(bar), "r"(0), "r"(c1), "r"(c2) : "memory");
}
__device__ __forceinline__ void tma_load_4d(uint32_t dst, const CUtensorMap* m, int c0, int c3, uint32_t bar) {
    asm volatile("cp.async.bulk.tensor.4d.shared::cluster.global.mbarrier::complete_tx::bytes [%0], [%1, {%3, %5, %5, %4}], [%2];"
                 ::"r"(dst), "l"(m), "r"(bar), "r"(c0), "r"(c3), "r"(0) : "memory");
}
__device__ __forceinline__ void wait_until(uint32_t t) {
    asm volatile("{\n\t.reg .pred p;\n\t.reg .s32 c;\nW:\n\tmov.u32 c, %%clock;\n\tsub.s32 c, %0, c;\n\tshr.s32 c, c, 2;\n\tsetp.gt.s32 p, c, 31;\n\t"
                 "@p nanosleep.u32 c;\n\t@p bra.uni W;\n\t}" ::"r"(t) : "memory");
}
__device__ __forceinline__ void tma_load_4d_both(uint32_t dst, const CUtensorMap* m, int c0, int c3, uint32_t bar) {
    asm volatile("cp.async.bulk.tensor.4d.shared::cluster.global.mbarrier::complete_tx::bytes.multicast::cluster [%0], [%1, {%3, %6, %6, %4}], [%2], %5;"
                 ::"r"(dst), "l"(m), "r"(bar), "r"(c0), "r"(c3), "h"((uint16_t)3), "r"(0) : "memory");
}
__device__ __forceinline__ void bulk_g2s(uint32_t dst, const void* src, uint32_t bytes, uint32_t bar) {
    asm volatile("cp.async.bulk.shared::cluster.global.mbarrier::complete_tx::bytes [%0], [%1], %2, [%3];"
                 ::"r"(dst), "l"(src), "r"(bytes), "r"(bar) : "memory");
}
__device__ __forceinline__ void fence_async() { asm volatile("fence.proxy.async.shared::cta;" ::: "memory"); }
__device__ __forceinline__ void named_sync(int id, int n) { asm volatile("bar.sync %0, %1;" ::"r"(id), "r"(n) : "memory"); }

__device__ __forceinline__ void ldsm4(uint32_t* r, uint32_t a) {
    asm volatile("ldmatrix.sync.aligned.m8n8.x4.shared.b16 {%0,%1,%2,%3}, [%4];"
                 : "=r"(r[0]), "=r"(r[1]), "=r"(r[2]), "=r"(r[3]) : "r"(a));
}
__device__ __forceinline__ void ldsm4t(uint32_t* r, uint32_t a) {
    asm volatile("ldmatrix.sync.aligned.m8n8.x4.trans.shared.b16 {%0,%1,%2,%3}, [%4];"
                 : "=r"(r[0]), "=r"(r[1]), "=r"(r[2]), "=r"(r[3]) : "r"(a));
}
__device__ __forceinline__ void stsm4t(uint32_t a, const uint32_t* r) {
    asm volatile("stmatrix.sync.aligned.m8n8.x4.trans.shared.b16 [%0], {%1,%2,%3,%4};"
                 ::"r"(a), "r"(r[0]), "r"(r[1]), "r"(r[2]), "r"(r[3]) : "memory");
}
__device__ __forceinline__ uint32_t lds32(uint32_t a) { uint32_t v; asm volatile("ld.shared.u32 %0, [%1];" : "=r"(v) : "r"(a)); return v; }
__device__ __forceinline__ uint32_t lds32v(uint32_t a) { uint32_t v; asm volatile("ld.volatile.shared.u32 %0, [%1];" : "=r"(v) : "r"(a)); return v; }
__device__ __forceinline__ float lds32f(uint32_t a) { float v; asm volatile("ld.shared.f32 %0, [%1];" : "=f"(v) : "r"(a)); return v; }
__device__ __forceinline__ uint2 lds64(uint32_t a) { uint2 v; asm volatile("ld.shared.v2.u32 {%0,%1}, [%2];" : "=r"(v.x), "=r"(v.y) : "r"(a)); return v; }
__device__ __forceinline__ uint4 lds128(uint32_t a) {
    uint4 v; asm volatile("ld.shared.v4.u32 {%0,%1,%2,%3}, [%4];" : "=r"(v.x), "=r"(v.y), "=r"(v.z), "=r"(v.w) : "r"(a)); return v;
}
template <int D> __device__ __forceinline__ void sts16x2(uint32_t a, float x) {
    asm volatile("{ .reg .b16 h; cvt.rn.bf16.f32 h, %1; st.shared.b16 [%0], h; st.shared.b16 [%0 + %2], h; }" ::"r"(a), "f"(x), "n"(D) : "memory");
}
__device__ __forceinline__ void sts32(uint32_t a, uint32_t v) { asm volatile("st.shared.u32 [%0], %1;" ::"r"(a), "r"(v) : "memory"); }
__device__ __forceinline__ void sts64(uint32_t a, uint32_t x, uint32_t y) { asm volatile("st.shared.v2.u32 [%0], {%1,%2};" ::"r"(a), "r"(x), "r"(y) : "memory"); }
__device__ __forceinline__ void sts128(uint32_t a, uint32_t x, uint32_t y, uint32_t z, uint32_t w) {
    asm volatile("st.shared.v4.u32 [%0], {%1,%2,%3,%4};" ::"r"(a), "r"(x), "r"(y), "r"(z), "r"(w) : "memory");
}
__device__ __forceinline__ void sts128f(uint32_t a, const float* c) {
    asm volatile("st.shared.v4.f32 [%0], {%1,%2,%3,%4};" ::"r"(a), "f"(c[0]), "f"(c[1]), "f"(c[2]), "f"(c[3]) : "memory");
}
__device__ __forceinline__ uint2 ldg64(const void* p) {
    uint2 v; asm volatile("ld.global.nc.L1::no_allocate.v2.u32 {%0,%1}, [%2];" : "=r"(v.x), "=r"(v.y) : "l"(p)); return v;
}
__device__ __forceinline__ uint32_t ldg16(const void* p) {
    uint16_t v; asm volatile("ld.global.nc.u16 %0, [%1];" : "=h"(v) : "l"(p)); return v;
}
__device__ __forceinline__ uint32_t ld_relaxed_32(const void* p) {
    uint32_t v; asm volatile("ld.relaxed.gpu.global.u32 %0, [%1];" : "=r"(v) : "l"(p) : "memory"); return v;
}
__device__ __forceinline__ uint2 ld_relaxed_64(const void* p) {
    uint2 v; asm volatile("ld.relaxed.gpu.global.v2.u32 {%0,%1}, [%2];" : "=r"(v.x), "=r"(v.y) : "l"(p) : "memory"); return v;
}
__device__ __forceinline__ uint4 ld_relaxed_128(const void* p) {
    uint4 v; asm volatile("ld.relaxed.gpu.global.v4.u32 {%0,%1,%2,%3}, [%4];" : "=r"(v.x), "=r"(v.y), "=r"(v.z), "=r"(v.w) : "l"(p) : "memory"); return v;
}
__device__ __forceinline__ void st_relaxed_32(void* p, uint32_t v) {
    asm volatile("st.relaxed.gpu.global.u32 [%0], %1;" ::"l"(p), "r"(v) : "memory");
}
__device__ __forceinline__ void st_relaxed_128(void* p, uint32_t x, uint32_t y, uint32_t z, uint32_t w) {
    asm volatile("st.relaxed.gpu.global.v4.u32 [%0], {%1,%2,%3,%4};" ::"l"(p), "r"(x), "r"(y), "r"(z), "r"(w) : "memory");
}
__device__ __forceinline__ void st_relaxed_64(void* p, uint32_t x, uint32_t y) {
    asm volatile("st.relaxed.gpu.global.u64 [%0], %1;" ::"l"(p), "l"((unsigned long long)x | ((unsigned long long)y << 32)) : "memory");
}
__device__ __forceinline__ void mma_bf16(float* c, uint32_t a0, uint32_t a1, uint32_t a2, uint32_t a3, uint32_t b0, uint32_t b1) {
    asm("mma.sync.aligned.m16n8k16.row.col.f32.bf16.bf16.f32 {%0,%1,%2,%3}, {%4,%5,%6,%7}, {%8,%9}, {%0,%1,%2,%3};"
                 : "+f"(c[0]), "+f"(c[1]), "+f"(c[2]), "+f"(c[3]) : "r"(a0), "r"(a1), "r"(a2), "r"(a3), "r"(b0), "r"(b1));
}
__device__ __forceinline__ void mma_bf16_z(float* c, uint32_t a0, uint32_t a1, uint32_t a2, uint32_t a3, uint32_t b0, uint32_t b1) {
    asm("mma.sync.aligned.m16n8k16.row.col.f32.bf16.bf16.f32 {%0,%1,%2,%3}, {%4,%5,%6,%7}, {%8,%9}, {%10,%10,%10,%10};"
        : "=f"(c[0]), "=f"(c[1]), "=f"(c[2]), "=f"(c[3]) : "r"(a0), "r"(a1), "r"(a2), "r"(a3), "r"(b0), "r"(b1), "f"(0.f));
}
__device__ __forceinline__ void mma_f16(float* c, const uint4& a, uint32_t b0, uint32_t b1) {
    asm("mma.sync.aligned.m16n8k16.row.col.f32.f16.f16.f32 {%0,%1,%2,%3}, {%4,%5,%6,%7}, {%8,%9}, {%0,%1,%2,%3};"
                 : "+f"(c[0]), "+f"(c[1]), "+f"(c[2]), "+f"(c[3]) : "r"(a.x), "r"(a.y), "r"(a.z), "r"(a.w), "r"(b0), "r"(b1));
}
__device__ __forceinline__ uint32_t pack_bf16(float lo, float hi) {
    uint32_t r; asm("cvt.rn.bf16x2.f32 %0, %1, %2;" : "=r"(r) : "f"(hi), "f"(lo)); return r;
}
__device__ __forceinline__ uint32_t pack_bf16v(float lo, float hi) {
    uint32_t r; asm("cvt.rn.satfinite.bf16x2.f32 %0, %1, %2;" : "=r"(r) : "f"(hi), "f"(lo)); return r;
}
__device__ __forceinline__ uint32_t pack_f16(float lo, float hi) {
    uint32_t r; asm("cvt.rn.f16x2.f32 %0, %1, %2;" : "=r"(r) : "f"(hi), "f"(lo)); return r;
}
__device__ __forceinline__ float bf_lo(uint32_t v) { return __uint_as_float(v << 16); }
__device__ __forceinline__ float bf_hi(uint32_t v) { return __uint_as_float(v & 0xffff0000u); }
__device__ __forceinline__ float bf_round(float x) { return __uint_as_float(pack_bf16(0.f, x)); }
__device__ __forceinline__ __nv_bfloat162 as_b2(uint32_t x) { return *reinterpret_cast<__nv_bfloat162*>(&x); }
__device__ __forceinline__ uint32_t as_u(__nv_bfloat162 x) { return *reinterpret_cast<uint32_t*>(&x); }
__device__ __forceinline__ uint32_t badd2(uint32_t a, uint32_t b) { uint32_t r; asm("add.rn.bf16x2 %0, %1, %2;" : "=r"(r) : "r"(a), "r"(b)); return r; }
__device__ __forceinline__ float rcpf(float x) { float r; asm("rcp.approx.ftz.f32 %0, %1;" : "=f"(r) : "f"(x)); return r; }
__device__ __forceinline__ float sqrtaf(float x) { float r; asm("sqrt.approx.ftz.f32 %0, %1;" : "=f"(r) : "f"(x)); return r; }
__device__ __forceinline__ float ex2f(float x) { float r; asm("ex2.approx.ftz.f32 %0, %1;" : "=f"(r) : "f"(x)); return r; }
constexpr float L2E = 1.4426950408889634f;
constexpr uint32_t ONES = 0x3f803f80u;

__device__ __forceinline__ uint2 recip2(uint32_t s2) {
    const uint32_t hi = pack_bf16(rcpf(bf_lo(s2)), rcpf(bf_hi(s2)));
    return make_uint2(hi, as_u(__hmul2(__hfma2(__hneg2(as_b2(s2)), as_b2(hi), as_b2(ONES)), as_b2(hi))));
}
__device__ __forceinline__ uint32_t normalize2(uint32_t x, __nv_bfloat162 m, __nv_bfloat162 rh, __nv_bfloat162 rl) {
    const __nv_bfloat162 d = __hsub2(as_b2(x), m);
    return as_u(__hfma2(d, rh, __hmul2(d, rl)));
}

__device__ __forceinline__ uint32_t unorder_key(uint32_t k16) { return k16 ^ ((k16 & 0x8000u) ? 0x8000u : 0xffffu); }

struct cplx { float r, i; };
__device__ __forceinline__ cplx csq(cplx a) { return {a.r * a.r - a.i * a.i, (a.r + a.r) * a.i}; }
__device__ __forceinline__ cplx csq_conj(cplx a) { return {a.r * a.r - a.i * a.i, (-a.r - a.r) * a.i}; }
__device__ __forceinline__ cplx cexpp(float a2, float th) {
    float m = ex2f(a2), s, c;
    __sincosf(th, &s, &c);
    return {m * c, m * s};
}
struct hc { __half2 r, i; };
__device__ __forceinline__ __half2 as_h2(uint32_t x) { return *reinterpret_cast<__half2*>(&x); }
__device__ __forceinline__ uint32_t as_u(__half2 x) { return *reinterpret_cast<uint32_t*>(&x); }
__device__ __forceinline__ hc hmul(hc a, hc b) {
    return {__hfma2(a.r, b.r, __hneg2(__hmul2(a.i, b.i))), __hfma2(a.r, b.i, __hmul2(a.i, b.r))};
}
__device__ __forceinline__ hc hpack(cplx a, cplx b) { return {as_h2(pack_f16(a.r, b.r)), as_h2(pack_f16(a.i, b.i))}; }
__device__ __forceinline__ void st_pair(uint32_t a, hc x, hc y) { sts128(a, as_u(x.r), as_u(x.i), as_u(y.r), as_u(y.i)); }
__device__ __forceinline__ void st_quad(uint32_t a, hc x, hc y) { sts128(a, as_u(x.r), as_u(y.r), as_u(x.i), as_u(y.i)); }

#define KSTAMP(i, dep) do { } while (0)
__device__ __forceinline__ void kgen_mma(float (&acc)[5][4], uint32_t priv, int lane, uint2 la, uint2 aim, uint2 cre, uint2 cim, float dt, uint32_t cs2) {
    const int g = lane >> 2, t = lane & 3;
#pragma unroll
    for (int i = 0; i < 5; i++) { acc[i][0] = acc[i][1] = acc[i][2] = acc[i][3] = 0.f; }
    const uint32_t wr = priv + lane * REC, rd = priv + 2 * t * REC;
    const float ndl = -dt * L2E;
#pragma unroll 1
    for (int ps = 0; ps < 2; ps++) {
        const uint32_t lw = ps ? la.y : la.x, iw = ps ? aim.y : aim.x;
        const uint32_t crw = as_u(__hmul2(as_b2(ps ? cre.y : cre.x), as_b2(cs2))), ciw = as_u(__hmul2(as_b2(ps ? cim.y : cim.x), as_b2(cs2)));
        const uint32_t ap = pack_bf16(ex2f(bf_lo(lw) * L2E), ex2f(bf_hi(lw) * L2E));
        const float a2[2] = {bf_lo(ap) * ndl, bf_hi(ap) * ndl}, th[2] = {bf_lo(iw) * dt, bf_hi(iw) * dt};
        cplx p1[2], p2[2], p4[2], p8[2], p32[2], p64[2], p128[2], p256[2], p512[2];
#pragma unroll
        for (int i = 0; i < 2; i++) {
            p1[i] = cexpp(a2[i], th[i]); p32[i] = cexpp(a2[i] * 32.f, th[i] * -32.f);
            p2[i] = csq(p1[i]); p4[i] = csq(p2[i]); p8[i] = csq_conj(p4[i]);
            p64[i] = csq(p32[i]); p128[i] = csq_conj(p64[i]); p256[i] = csq(p128[i]); p512[i] = csq(p256[i]);
        }
        const hc C = {as_h2(pack_f16(bf_lo(crw), bf_hi(crw))), as_h2(pack_f16(bf_lo(ciw), bf_hi(ciw)))};
        const hc z1 = hpack(p1[0], p1[1]), z2 = hpack(p2[0], p2[1]), z4 = hpack(p4[0], p4[1]);
        const hc y8 = hpack(p8[0], p8[1]), y32 = hpack(p32[0], p32[1]), y64 = hpack(p64[0], p64[1]);
        const hc z128 = hpack(p128[0], p128[1]), z256 = hpack(p256[0], p256[1]), z512 = hpack(p512[0], p512[1]);
        KSTAMP(8 + 3 * ps, z512.r);
        __syncwarp();
        const hc c1 = hmul(C, z1), c2 = hmul(C, z2), c5 = hmul(c1, z4), c6 = hmul(c2, z4);
        st_pair(wr + 160, hmul(c1, z128), hmul(c2, z128));
        st_pair(wr + 128, c1, c2);
        st_pair(wr + 176, hmul(c5, z128), hmul(c6, z128));
        st_pair(wr + 144, c5, c6);
        const hc y16 = hmul(y8, y8), y48 = hmul(y16, y32), y24 = hmul(y16, y8), y40 = hmul(y32, y8), y56 = hmul(y48, y8), y72 = hmul(y64, y8);
        st_quad(wr, {as_h2(0x3c003c00u), as_h2(0u)}, y8);
        st_quad(wr + 80, hmul(y64, y16), hmul(y64, y24));
        st_quad(wr + 16, y16, y24);
        st_quad(wr + 96, hmul(y64, y32), hmul(y64, y40));
        st_quad(wr + 32, y32, y40);
        st_quad(wr + 112, hmul(y64, y48), hmul(y64, y56));
        st_quad(wr + 48, y48, y56);
        st_quad(wr + 64, y64, y72);
        const hc z258 = hmul(z256, z2);
        st_pair(wr + 192, hmul(z256, z1), z258);
        st_pair(wr + 224, z2, hmul(z512, z4));
        st_pair(wr + 240, z2, hmul(z512, z512));
        st_pair(wr + 208, z258, z512);
        KSTAMP(9 + 3 * ps, z512.r);
        __syncwarp();
#pragma unroll KGU
        for (int k2 = 0; k2 < 4; k2++) {
#pragma unroll
            for (int s = 0; s < 2; s++) {
                const uint32_t o = rd + k2 * 8 * REC + s * REC;
                const uint4 A = lds128(o + 16 * g);
                const uint2 h = lds64(o + 128 + 8 * g);
                const uint4 M = lds128(o + 192 + 16 * (g & 1)), N = lds128(o + 224 + 8 * (g & 2));
                const hc H0 = {as_h2(h.x), as_h2(h.y)};
                const hc H1 = hmul(H0, {as_h2(N.x), as_h2(N.y)}), H2 = hmul(H0, {as_h2(M.x), as_h2(M.y)});
                const hc H3 = hmul(H2, {as_h2(M.z), as_h2(M.w)}), H4 = hmul(H3, {as_h2(N.z), as_h2(N.w)});
                mma_f16(acc[0], A, h.x, h.y);
                mma_f16(acc[1], A, as_u(H1.r), as_u(H1.i));
                mma_f16(acc[2], A, as_u(H2.r), as_u(H2.i));
                mma_f16(acc[3], A, as_u(H3.r), as_u(H3.i));
                mma_f16(acc[4], A, as_u(H4.r), as_u(H4.i));
            }
        }
        KSTAMP(10 + 3 * ps, z512.r);
    }
}

__device__ __forceinline__ void kgen_tables(const float (&acc)[5][4], uint32_t priv, int lane, float scale, float k0) {
    const int g = lane >> 2, t0 = lane & 1, t1 = (lane >> 1) & 1;
    __syncwarp();
    sts128(priv + 16 * lane + (lane < 17 ? T_PATCH - 48 : T_S4 + 608 - 272), 0, 0, 0, 0);
    if (lane < 20) sts128(priv + 16 * lane + (lane < 16 ? 0 : T_DENSE - 256), 0, 0, 0, 0);
    uint32_t w2[2], w3[2], w4[2], ab[2], W[2], pv[2];
#pragma unroll
    for (int hf = 0; hf < 2; hf++) {
        const float k1 = acc[0][2 * hf] * scale, k2 = acc[0][2 * hf + 1] * scale, k3 = acc[1][2 * hf] * scale, k4 = acc[1][2 * hf + 1] * scale;
        w2[hf] = pack_bf16(k2, k1); w3[hf] = pack_bf16(k3, k2); w4[hf] = pack_bf16(k4, k3);
        ab[hf] = pack_bf16(acc[2][2 * hf + 1] * scale, acc[2][2 * hf] * scale);
        W[hf] = __byte_perm(w4[hf], ab[hf], 0x5410);
    }
    pv[1] = __shfl_xor_sync(0xffffffffu, t0 ? W[0] : W[1], 1);
    pv[0] = __shfl_sync(0xffffffffu, t0 ? W[1] : W[0], t0 ? lane - 1 : lane < 4 ? 31 - lane : lane - 3);
    const uint32_t kk = pack_bf16(k0, 0.f);
    if (lane == 0) pv[0] = __byte_perm(kk, pv[0], 0x5410);
    const uint32_t pd = priv + T_DENSE + 64 + 512 * t1 + 64 * g + 16 * t0;
#pragma unroll
    for (int hf = 0; hf < 2; hf++) {
        sts128(pd + 32 * hf, __byte_perm(w2[hf], pv[hf], 0x5432), w2[hf], w3[hf], w4[hf]);
        sts128(pd + 32 * hf + 1024, __byte_perm(pv[hf], 0, 0x3232), __byte_perm(ab[hf], pv[hf], 0x7632), ab[hf], __byte_perm(ab[hf], 0, 0x1010));
    }
    __syncwarp();
    const uint32_t p4 = priv + T_S4 + 16 * (6 + g + 8 * t1) + 4 * (t0 ^ 1), p8 = priv + T_S8 + 8 * (6 + g + 8 * t1 + 32 * t0);
#pragma unroll
    for (int i = 0; i < 4; i++) {
        sts16x2<18>(p4 + 256 * (i & 1) + 8 * (i >> 1), acc[3][i] * scale);
        sts16x2<10>(p8 + 128 * (i & 1) + 4 * (i >> 1), acc[4][i] * scale);
    }
    if (lane == 31) {
        const uint32_t aa = __byte_perm(ab[1], 0, 0x1010), c3 = pack_bf16(acc[3][3] * scale, 0.f);
        sts32(priv + T_DENSE + 60, kk);
        sts128(priv + T_PATCH - 64, aa, aa, aa << 16, 0u);
        sts128(priv + T_PATCH + 48, c3, c3 * 0x10001u, c3 << 16, 0u);
    }
    __syncwarp();
}

__device__ __forceinline__ void dense_phase(float (&acc)[16][4], uint32_t priv, int lane) {
    const int m = lane >> 3, r = lane & 7;
    const uint32_t vrow = priv + 256;
    const uint32_t pb = priv + T_DENSE + 4 * (15 + (lane >> 2) - 2 * (lane & 3));
    const int off0 = 256 * (lane >> 4) + 32 * r + 16 * (m & 1);
    float B[8][4];
#pragma unroll
    for (int i = 0; i < 8; i++) { B[i][0] = B[i][1] = B[i][2] = B[i][3] = 0.f; }
#pragma unroll
    for (int i = 0; i < 16; i++) { acc[i][0] = acc[i][1] = acc[i][2] = acc[i][3] = 0.f; }
    auto ld_frag = [](uint32_t (&T)[4], uint32_t q) { T[0] = lds32(q); T[1] = lds32(q + 32); T[2] = lds32(q - 32); T[3] = lds32v(q); };
    auto ld_swap = [](uint32_t (&T)[4], uint32_t q) { T[2] = lds32(q); T[3] = lds32(q + 32); T[0] = lds32(q - 32); T[1] = lds32v(q); };
    auto add_frag = [](uint32_t (&S)[4], const uint32_t (&E)[4], const uint32_t (&O)[4]) {
        S[0] = badd2(E[0], O[1]); S[1] = badd2(E[1], O[3]); S[2] = badd2(E[2], O[0]); S[3] = badd2(E[3], O[2]);
    };
    int off = (off0 ^ (lane & 16)) - 32;
    uint32_t pq = pb + 64, a1 = vrow + (off ^ ((off >> 3) & 16));
    uint32_t T2[4], T3[4], R[8][4];
    ld_frag(T2, pq + 1024); ld_swap(T3, pq + 1536);
#pragma unroll
    for (int i = 0; i < NPRE; i++) ldsm4(R[i], a1 + i * 512);
#pragma unroll 1
    for (int rho = 1; rho <= 8; rho++) {
        uint32_t T0[4], T1[4], S[4], s[8][2];
#pragma unroll
        for (int i = NPRE; i < 8; i++) ldsm4(R[i], a1 + i * 512);
        ld_frag(T0, pq); ld_swap(T1, pq + 512);
        off -= 32; pq += 64;
        a1 = vrow + (off ^ ((off >> 3) & 16));
        add_frag(S, T2, T3);
#pragma unroll
        for (int i = 0; i < 8; i++) {
            s[i][0] = badd2(R[i][0], R[i][3]); s[i][1] = badd2(R[i][1], R[i][2]);
            if (i < 7) {
                mma_bf16(acc[2 * i + 2], T2[0], T2[1], T2[2], T2[3], R[i][0], R[i][1]);
                mma_bf16(B[i + 1], T3[0], T3[1], T3[2], T3[3], R[i][2], R[i][3]);
                mma_bf16(acc[2 * i + 3], S[0], S[1], S[2], S[3], s[i][0], s[i][1]);
            }
        }
        ld_frag(T2, pq + 1024); ld_swap(T3, pq + 1536);
        add_frag(S, T0, T1);
#pragma unroll
        for (int i = 0; i < 8; i++) {
            mma_bf16(acc[2 * i], T0[0], T0[1], T0[2], T0[3], R[i][0], R[i][1]);
            mma_bf16(B[i], T1[0], T1[1], T1[2], T1[3], R[i][2], R[i][3]);
            mma_bf16(acc[2 * i + 1], S[0], S[1], S[2], S[3], s[i][0], s[i][1]);
            if (i < NPRE) ldsm4(R[i], a1 + i * 512);
        }
    }
    KSTAMP(14, as_h2(0u));
#pragma unroll
    for (int i = 0; i < 8; i++)
#pragma unroll
        for (int j = 0; j < 4; j++) {
            acc[2 * i + 1][j] = (acc[2 * i + 1][j] - acc[2 * i][j]) - B[i][j];
            if (i) acc[2 * i][j] += B[i - 1][j];
        }
    const uint32_t a = vrow + (off0 ^ ((off0 >> 3) & 16));
    uint32_t Q[4], N[4];
    ld_frag(Q, pb);
    const uint32_t pp = pb + T_PATCH - T_DENSE - 24;
    ld_frag(N, pp);
#pragma unroll
    for (int i = 0; i < 8; i++) {
        uint32_t V[4];
        ldsm4(V, a + i * 512);
        mma_bf16(acc[2 * i], Q[0], Q[1], Q[2], Q[3], V[0], V[1]);
        mma_bf16(acc[2 * i + 1], Q[0], Q[1], Q[2], Q[3], V[2], V[3]);
        if (i < 4) {
            mma_bf16(acc[2 * i + 8], N[0], N[1], N[2], N[3], V[0], V[1]);
            mma_bf16(acc[2 * i + 9], N[0], N[1], N[2], N[3], V[2], V[3]);
        }
    }
    const int ofm = (off0 | 16) - 32;
    const uint32_t b = vrow + (ofm ^ ((ofm >> 3) & 16));
    const uint32_t bz = (m & 1) ? priv : b, bm = (m & 1) ? b : b + 1024;
    const uint32_t m0 = lds32(pb + 4 * 520), m1 = lds32(pb + 4 * 528), m2 = lds32v(pp + 32), m3 = lds32(pp + 64);
#pragma unroll
    for (int i = 0; i < 6; i++) {
        uint32_t V[4];
        ldsm4(V, i < 2 ? bz + ((m & 1) ? 0 : i * 512) : bm + (i - 2) * 512);
        mma_bf16(acc[2 * i + 4], m0, m1, m2, m3, V[0], V[1]);
        mma_bf16(acc[2 * i + 5], m0, m1, m2, m3, V[2], V[3]);
    }
}

__device__ __forceinline__ uint32_t ones2(int c, int lo, int n) {
    return (((uint32_t)(c - lo) < (uint32_t)n) ? 0x3f80u : 0u) | (((uint32_t)(c + 1 - lo) < (uint32_t)n) ? 0x3f800000u : 0u);
}
struct Box { uint32_t q[4], ad[4]; };
template <int O, int L1, int N1, int L2, int N2>
__device__ __forceinline__ void box_setup(Box& bx, uint32_t priv, int lane) {
    const int g = lane >> 2, t = lane & 3, d = 2 * t - g;
    bx.q[0] = ones2(d, L1, N1); bx.q[1] = ones2(d, L2, N2); bx.q[2] = ones2(d + 8, L1, N1); bx.q[3] = ones2(d + 8, L2, N2);
#pragma unroll
    for (int i = 0; i < 4; i++) {
        const int T = 16 * g + O + 8 * i + 2 * t;
        bx.ad[i] = priv + 256 + ((2 * T) ^ ((T >> 2) & 16));
    }
}
__device__ __forceinline__ void box_mma(float (&X)[4], float (&Y)[4], float (&Z)[4], const Box& bx, int G) {
    mma_bf16_z(Z, bx.q[0], bx.q[1], bx.q[2], bx.q[3], lds32(bx.ad[0] + 256 * G), lds32v(bx.ad[1] + 256 * G));
    mma_bf16_z(X, bx.q[0], bx.q[1], bx.q[2], bx.q[3], lds32(bx.ad[1] + 256 * G), lds32v(bx.ad[2] + 256 * G));
    mma_bf16_z(Y, bx.q[0], bx.q[1], bx.q[2], bx.q[3], lds32(bx.ad[2] + 256 * G), lds32(bx.ad[3] + 256 * G));
}
template <int G0, int G1>
__device__ __forceinline__ void tail4(float (&acc)[16][4], const Box& bx, const uint4 (&B)[5]) {
#pragma unroll
    for (int G = G0; G < G1; G++) {
        float X[4], Y[4], Z[4];
        box_mma(X, Y, Z, bx, G);
        const uint32_t a0 = pack_bf16(X[0], X[1]), a1 = pack_bf16(Y[0], Y[1]), a2 = pack_bf16(X[2], X[3]), a3 = pack_bf16(Y[2], Y[3]);
        const uint32_t c0 = pack_bf16(Z[0], Z[1]), c1 = pack_bf16v(X[0], X[1]), c2 = pack_bf16(Z[2], Z[3]), c3 = pack_bf16v(X[2], X[3]);
#pragma unroll
        for (int b = 0; b < 5; b++)
            if (G + 4 + b < 16) mma_bf16(acc[G + 4 + b], a0, a1, a2, a3, B[b].x, B[b].y);
#pragma unroll
        for (int b = 0; b < 5; b++)
            if (G + 4 + b < 16) mma_bf16(acc[G + 4 + b], c0, c1, c2, c3, B[b].z, B[b].w);
    }
}
template <int G0, int G1>
__device__ __forceinline__ void tail8(float (&acc)[16][4], const Box& bx, const uint2 (&B)[8]) {
#pragma unroll
    for (int G = G0; G < G1; G++) {
        float X[4], Y[4], Z[4];
        box_mma(X, Y, Z, bx, G);
        const uint32_t a0 = pack_bf16(X[0], X[1]), a1 = pack_bf16(Y[0], Y[1]), a2 = pack_bf16(Z[2], Z[3]), a3 = pack_bf16(X[2], X[3]);
#pragma unroll
        for (int b = 0; b < 8 - G; b++) mma_bf16(acc[G + 8 + b], a0, a1, a2, a3, B[b].x, B[b].y);
    }
}

__device__ __forceinline__ uint32_t mean_std(float mu, float var) { return pack_bf16(mu, sqrtaf(bf_round(bf_round(var) + 1e-5f))); }
__device__ __noinline__ uint2 ln_centred(uint32_t sb, float mu) {
    const int lane = threadIdx.x & 31;
    uint32_t ms = 0;
    float res = 0.f, ri = 0.f;
#pragma unroll 1
    for (int mode = 0; mode < 2; mode++) {
#pragma unroll 1
        for (int rr = 0; rr < 16; rr++) {
            const float c0 = __shfl_sync(0xffffffffu, mu, rr), rj = __shfl_sync(0xffffffffu, ri, rr);
            float c = 0.f;
#pragma unroll 1
            for (int k = 0; k < 16; k++) {
                const uint32_t q = lds32(sb + OFF_ROWS + k * 2048 + rr * 128 + ((lane * 4) ^ ((rr & 7) << 4))), wq = lds32(sb + OFF_GP + k * 128 + lane * 4);
                const float d0 = bf_lo(q) - c0, d1 = bf_hi(q) - c0;
                if (mode) c = fmaf(bf_round(bf_round(d0) * rj), bf_lo(wq), fmaf(bf_round(bf_round(d1) * rj), bf_hi(wq), c));
                else c = fmaf(d0, d0, fmaf(d1, d1, c));
            }
#pragma unroll 1
            for (int o = 16; o; o >>= 1) c += __shfl_xor_sync(0xffffffffu, c, o);
            if ((lane & 15) == rr) res = c;
        }
        if (mode == 0) { ms = mean_std(mu, res * (1.f / DM)); mu = bf_lo(ms); ri = rcpf(bf_hi(ms)); }
    }
    named_sync(1, 128);
    return make_uint2(ms, __float_as_uint(res));
}

__device__ __forceinline__ void router_cta(uint32_t* scr, uint32_t sb, uint32_t zero, int tid, int warp) {
    const int lane = tid & 31;
    const uint32_t cand = sb + 128;
    const uint32_t epoch = ld_relaxed_32(scr + S_EPOCH);
    if (tid < 128) st_relaxed_32(scr + S_SEL + tid, 0u);
    if (tid == 0) sts32(sb + 64, cand);
    sts128(cand + 16 * tid, 0, 0, 0, 0);
    asm volatile("fence.acq_rel.gpu;" ::: "memory");
    const uint32_t tag = (epoch + 1u) | 0x8000u;
    STAMP(0); GSTAMP(1);
    uint32_t* const psel = scr + S_SEL + 32 * (lane & 3);
    const uint32_t cnt = sb + 64 + (tid & zero);
    uint32_t it = 0;
    uint4 q;
#pragma unroll 1
    do {
        q = ld_relaxed_128(scr + S_KEY + 4 * tid);
        if (++it > SPIN_LIMIT) __trap();
    } while (!__all_sync(0xffffffffu, (((q.x ^ tag) | (q.y ^ tag) | (q.z ^ tag) | (q.w ^ tag)) & 0xffffu) == 0));
    STAMP(2);
    uint32_t key[4] = {q.x, q.y, q.z, q.w};
#pragma unroll
    for (int j = 0; j < 4; j++) key[j] = ((key[j] ^ ((uint32_t)((int)key[j] >> 31) | 0x80000000u)) & 0xffff0000u) | (0xffffu - (uint32_t)(4 * tid + j));
    const uint32_t gm = __reduce_max_sync(0xffffffffu, max(max(key[0], key[1]), max(key[2], key[3])));
    sts32(sb + 4 * warp, gm);
    __syncthreads();
    const uint2 pr = lds64(sb + 8 * (lane & 7));
    const uint32_t tau = __reduce_min_sync(0xffffffffu, max(pr.x, pr.y));
    asm volatile("{\n\t.reg .pred p<4>;\n\t.reg .u32 a<4>;\n\t"
                 "setp.ge.u32 p0, %0, %4;\n\tsetp.ge.u32 p1, %1, %4;\n\tsetp.ge.u32 p2, %2, %4;\n\tsetp.ge.u32 p3, %3, %4;\n\t"
                 "@p0 atom.shared.add.u32 a0, [%5], 4;\n\t@p1 atom.shared.add.u32 a1, [%5], 4;\n\t"
                 "@p2 atom.shared.add.u32 a2, [%5], 4;\n\t@p3 atom.shared.add.u32 a3, [%5], 4;\n\t"
                 "@p0 st.shared.u32 [a0], %0;\n\t@p1 st.shared.u32 [a1], %1;\n\t@p2 st.shared.u32 [a2], %2;\n\t@p3 st.shared.u32 [a3], %3;\n\t}"
                 ::"r"(key[0]), "r"(key[1]), "r"(key[2]), "r"(key[3]), "r"(tau), "r"(cnt) : "memory");
    __syncthreads();
    STAMP(6);
    const uint32_t c0 = lds32v(cand + 4 * lane);
    uint2 k = lds64(cand + 8 * warp);
    const uint32_t end = __shfl_sync(0xffffffffu, lds32v(sb + 64), 0);
    uint32_t i = cand + 8 * warp;
#pragma unroll 1
    do {
        uint32_t r0 = __popc(__ballot_sync(0xffffffffu, c0 > k.x)), r1 = __popc(__ballot_sync(0xffffffffu, c0 > k.y));
#pragma unroll 1
        for (uint32_t j = cand + 128; j < end; j += 128) {
            const uint32_t c = lds32(j + 4 * lane);
            r0 += __popc(__ballot_sync(0xffffffffu, c > k.x)); r1 += __popc(__ballot_sync(0xffffffffu, c > k.y));
        }
        const uint32_t rk = (lane & 4) ? r1 : r0;
        if (rk < 8 && lane < 8) st_relaxed_64(psel + 2 * rk, (lane & 4) ? k.y : k.x, tag);
        i += 128;
        k = lds64(i);
    } while (i < end);
    STAMP(4); GSTAMP(5);
    if (tid == 0) st_relaxed_32(scr + S_EPOCH, epoch + 1u);
}

__global__ void __cluster_dims__(2, 1, 1) __launch_bounds__(NTHR, 1)
fused_kernel(const __grid_constant__ Ptrs p, const __grid_constant__ Maps maps) {
    extern __shared__ __align__(1024) unsigned char smem[];
    const uint32_t sb = s_u32(smem);
    const int tid = threadIdx.x, lane = tid & 31;
    const int warp = __shfl_sync(0xffffffffu, tid >> 5, 0);
    const int b = blockIdx.x, h = b & 1, cl = b >> 1;
    const uint32_t bar0 = sb + OFF_BAR;
    const int m = lane >> 3, r = lane & 7;
    if (b >= NCTA) {
        if (b == NCTA) router_cta(p.scr, sb, p.zero, tid, warp);
        return;
    }
    if (warp < 8) {
        const int w = warp, dch = 8 * b + w;
        STAMP(0);
        if (INC_AT == 0) asm volatile("setmaxnreg.inc.sync.aligned.u32 %0;" ::"n"(NREG));
        const int po = dch * NMODE + 4 * lane;
        const uint2 la = ldg64(p.logA + po), aim = ldg64(p.Aim + po), cre = ldg64(p.Cre + po), cim = ldg64(p.Cim + po);
        const uint32_t ldt16 = ldg16(p.ldt + dch), dsk16 = ldg16(p.dsk + dch);
        cluster_arrive();
        if (INC_AT == 1) asm volatile("setmaxnreg.inc.sync.aligned.u32 %0;" ::"n"(NREG));
        const uint32_t priv = sb + OFF_PRIV + w * PRIV;
        const int g = lane >> 2, t = lane & 3;
        const uint32_t* sp = p.scr + S_STAT + 2048 * (cl & 3) + 256 * w + 16 * t + 2 * g;
        uint2 sq[4];
        {
            const uint32_t m2 = as_u(__hmax2(__hmax2(__habs2(as_b2(cre.x)), __habs2(as_b2(cre.y))), __hmax2(__habs2(as_b2(cim.x)), __habs2(as_b2(cim.y)))));
            const uint32_t eb = min(max(__reduce_max_sync(0xffffffffu, max(m2 << 16, m2)) >> 23, 1u), 252u);
            const float dt = bf_round(ex2f(bf_lo(ldt16) * L2E));
            float s0[4];
            mma_bf16_z(s0, ONES, ONES, ONES, ONES, cre.x, cre.y);
            STAMP(1);
            float kacc[5][4];
            kgen_mma(kacc, priv, lane, la, aim, cre, cim, dt, (253u - eb) * 0x00800080u);
            STAMP(2);
            cluster_wait();
            if (INC_AT == 2) asm volatile("setmaxnreg.inc.sync.aligned.u32 %0;" ::"n"(NREG));
            if (elect_one()) mbar_arrive(bar0 + 8 * B_KG);
#pragma unroll
            for (int i = 0; i < 4; i++) sq[i] = ld_relaxed_64(sp + 64 * i);
            float k0 = s0[0] + s0[1];
            k0 += __shfl_xor_sync(0xffffffffu, k0, 1);
            k0 += __shfl_xor_sync(0xffffffffu, k0, 2);
            kgen_tables(kacc, priv, lane, (dt + dt) * __uint_as_float((eb + 1u) << 23), fmaf(k0, dt + dt, bf_lo(dsk16) + 1.f));
        }
        STAMP(3);
        {
            mbar_wait(bar0 + 8 * B_TAG, 0);
            const uint32_t want = lds32(sb + OFF_MISC);
            uint32_t s2[4];
#pragma unroll 1
            while (true) {
#pragma unroll
                for (int i = 0; i < 4; i++) s2[i] = __byte_perm(sq[i].x, sq[i].y, 0x7632) ^ want;
                if (__all_sync(0xffffffffu, ((s2[0] | s2[1] | s2[2] | s2[3]) & 0x80008000u) == 0)) break;
#pragma unroll
                for (int i = 0; i < 4; i++) sq[i] = ld_relaxed_64(sp + 64 * i);
            }
            STAMP(4);
            mbar_wait(bar0 + 8 * (B_X + w), 0);
            STAMP(5);
            uint32_t v[8][4];
#pragma unroll
            for (int i = 0; i < 4; i++) {
                const uint2 rc = recip2(s2[i]);
#pragma unroll
                for (int hf = 0; hf < 2; hf++) {
                    const __nv_bfloat162 mm = __low2bfloat162(as_b2(hf ? sq[i].y : sq[i].x));
                    const __nv_bfloat162 rh = hf ? __high2bfloat162(as_b2(rc.x)) : __low2bfloat162(as_b2(rc.x));
                    const __nv_bfloat162 rl = hf ? __high2bfloat162(as_b2(rc.y)) : __low2bfloat162(as_b2(rc.y));
                    const uint4 q = lds128(sb + OFF_X + 8192 * w + 32 * lane + ((h ^ (g & 1)) << 4) + 2048 * i + 1024 * hf);
                    uint32_t* o = v[2 * i + hf];
                    o[0] = normalize2(q.x, mm, rh, rl); o[1] = normalize2(q.y, mm, rh, rl); o[2] = normalize2(q.z, mm, rh, rl); o[3] = normalize2(q.w, mm, rh, rl);
                }
            }
            mbar_wait(bar0 + 8 * B_KG, 0);
            const uint32_t dst = sb + OFF_PRIV + (2 * m + (r & 1)) * PRIV + 256 + 512 * w + 32 * (r >> 1);
#pragma unroll
            for (int i = 0; i < 8; i++) stsm4t(dst + 128 * (i >> 1) + 16 * ((i ^ (i >> 1)) & 1), v[i]);
            __syncwarp();
            if (elect_one()) { mbar_arrive(bar0 + 8 * B_VT); mbar_arrive_peer(mapa(bar0 + 8 * B_PV, h ^ 1)); }
            __syncwarp();
            if (INC_AT == 3) asm volatile("setmaxnreg.inc.sync.aligned.u32 %0;" ::"n"(NREG));
            mbar_wait(bar0 + 8 * B_VT, 0);
        }
        STAMP(6);
        float acc[16][4];
        dense_phase(acc, priv, lane);
        STAMP(7);
        const uint32_t sd = sb + OFF_X + 512 * (8 * h + w) + 16 * (lane ^ (2 * (w & 1) + 4 * h));
        const uint32_t sd0 = mapa(sd + 8192, 0), sd1 = mapa(sd, 1);
        auto send = [&](auto PT) {
            constexpr int pt = decltype(PT)::value;
#pragma unroll
            for (int i = 0; i < 2; i++) {
                const float* c0 = acc[4 * pt + 2 * i];
                const float* c1 = acc[4 * pt + 2 * i + 1];
                asm volatile("st.async.weak.shared::cluster.mbarrier::complete_tx::bytes.v4.b32 [%0 + %6], {%1,%2,%3,%4}, [%5];"
                             ::"r"(i ? sd1 : sd0), "r"(pack_bf16(c0[0], c0[1])), "r"(pack_bf16(c0[2], c0[3])), "r"(pack_bf16(c1[0], c1[1])),
                               "r"(pack_bf16(c1[2], c1[3])), "r"(mapa(bar0 + 8 * (B_RECV + pt), i)), "n"(16384 * pt) : "memory");
            }
        };
        const uint32_t low = 64 * (t >> 1) + 32 * (g & 1) + 16 * (t & 1), stg = (priv + T_DENSE + 111) & ~127u;
        const uint32_t xa = sb + OFF_X + 16384 * (w >> 2) + 8192 * h + 256 * (w & 3) + 128 * (lane & 24) + 128 * (lane & 16) + low;
        const uint32_t sa = sb + OFF_X + 16384 * (w >> 2) + 8192 * (h ^ 1) + 128 * (w & 3) + 512 * (4 * (r & 2) + 2 * m + (r & 1)) + 16 * ((r >> 2) ^ (2 * (r & 3)));
        const uint32_t so = stg + 32 * (lane & 24) + 32 * (lane & 16) + low;
        auto finish = [&](int ph) {
            if (ph == FINE) STAMP(1);
            const int box = 4 * ph + 2 * (w >> 2) + h;
            uint4 x[4];
            uint32_t s[4][4];
#pragma unroll
            for (int i = 0; i < 4; i++) x[i] = lds128((xa ^ (8 * (i & 2))) + 32768 * ph + 2048 * (i & 1) + 64 * (i & 2));
            if (ph == FINE) STAMP(2);
            mbar_wait(bar0 + 8 * (B_RECV + 2 * ph + (w >> 2)), 0);
            if (ph == FINE) STAMP(3);
            const uint32_t routed = __shfl_sync(0xffffffffu, lds32(sb + OFF_MISC + 4), 0);
#pragma unroll
            for (int i = 0; i < 4; i++) ldsm4t(s[i], (sa ^ (32 * i)) + 32768 * ph);
#pragma unroll
            for (int i = 0; i < 4; i++) { s[i][0] = badd2(x[i].x, s[i][0]); s[i][1] = badd2(x[i].y, s[i][1]); s[i][2] = badd2(x[i].z, s[i][2]); s[i][3] = badd2(x[i].w, s[i][3]); }
            if (ph == FINE) STAMP(4);
            if ((routed >> (4 * box + (w & 3))) & 1) {
                const uint32_t tk = 256 * box + 128 * (g >> 2) + 32 * (t >> 1) + 16 * (g & 1) + 4 * (g & 2) + 2 * (w & 3);
                const uint32_t mk[2] = {lds32(sb + OFF_MISC + 32 + 4 * (tk >> 5)) >> (tk & 31), lds32(sb + OFF_MISC + 40 + 4 * (tk >> 5)) >> (tk & 31)};
                __nv_bfloat16* o = p.out + (size_t)tk * DM + 16 * cl + 8 * (t & 1);
#pragma unroll
                for (int i = 0; i < 4; i++)
                    asm volatile("{\n\t.reg .pred p;\n\tsetp.eq.u32 p, %6, 0;\n\t@!p st.shared.v4.u32 [%1], {%2,%3,%4,%5};\n\t@p st.global.v4.u32 [%0], {%2,%3,%4,%5};\n\t}"
                                 ::"l"(o + (64 * (i & 1) + (i >> 1)) * DM), "r"((xa ^ (8 * (i & 2))) + 32768 * ph + 2048 * (i & 1) + 64 * (i & 2)),
                                   "r"(s[i][0]), "r"(s[i][1]), "r"(s[i][2]), "r"(s[i][3]), "r"(mk[i & 1] & (1u << (i >> 1))) : "memory");
            } else {
#pragma unroll
                for (int i = 0; i < 4; i++) sts128(so - 2048 * ph + 512 * (i & 1) + 64 * (i & 2), s[i][0], s[i][1], s[i][2], s[i][3]);
                fence_async();
                if (ph == FINE) STAMP(5);
                __syncwarp();
                if (elect_one()) {
                    asm volatile("cp.async.bulk.tensor.5d.global.shared::cta.bulk_group [%0, {%2, %5, %3, %5, %4}], [%1];"
                                 ::"l"(&maps.out), "r"(stg - 2048 * ph), "r"(16 * cl), "r"(2 * (w & 3)), "r"(4 * box), "r"(0) : "memory");
                }
            }
        };
        mbar_wait(bar0 + 8 * B_PV, 0);
        send(IC<0>());
        {
            Box bx;
            box_setup<-18, 0, 5, 5, 3>(bx, priv, lane);
            uint4 B[5];
#pragma unroll
            for (int i = 0; i < 5; i++) B[i] = lds128(priv + T_S4 + 16 * (6 + 8 * i + g - 2 * t));
            tail4<0, 4>(acc, bx, B);
            send(IC<1>());
            STAMP(8);
            tail4<4, FIN_A>(acc, bx, B);
            STAMP(9);
            finish(0);
            STAMP(10);
            tail4<FIN_A, 12>(acc, bx, B);
        }
        {
            Box bx;
            box_setup<-20, 1, 7, 0, 9>(bx, priv, lane);
            uint2 B[8];
#pragma unroll
            for (int i = 0; i < 8; i++) B[i] = lds64(priv + T_S8 + 8 * (6 + 8 * i + g - 2 * t));
            tail8<0, 4>(acc, bx, B);
            send(IC<2>());
            tail8<4, 8>(acc, bx, B);
        }
        STAMP(11);
        send(IC<3>());
        finish(1);
        STAMP(12);
        __syncwarp();
        if (elect_one()) mbar_arrive(bar0 + 8 * B_ST);
        cluster_arrive();
        asm volatile("cp.async.bulk.commit_group;" ::: "memory");
        asm volatile("cp.async.bulk.wait_group.read 0;" ::: "memory");
        STAMP(13); GSTAMP(15);
    } else if (warp < 12) {
        const int a = warp - 8, at = 32 * a + lane, g = lane >> 2, t = lane & 3;
        STAMP(0);
        if (elect_one()) {
            const uint32_t cnt = a == 3 ? 0x18411122u : 0x11111111u, tx = a == 0 ? 0x44444444u : a == 3 ? 0x00084444u : 0u;
#pragma unroll 1
            for (int i = 0; i < 8; i++) {
                mbar_init(bar0 + 64 * a + 8 * i, (cnt >> (4 * i)) & 15);
                const uint32_t n = (tx >> (4 * i)) & 15;
                if (n) mbar_expect_tx(bar0 + 64 * a + 8 * i, n << 11);
            }
            if (a < 3) mbar_init(bar0 + 8 * (B_KG + a), 8);
            asm volatile("fence.mbarrier_init.release.cluster;" ::: "memory");
            fence_async();
        }
        __syncwarp();
        cluster_arrive();
        const uint32_t epoch = ld_relaxed_32(p.scr + S_EPOCH);
        uint32_t* const pst = p.scr + S_STAT + 2048 * a + 16 * b + 2 * r + m;
        uint32_t* const pky = p.scr + S_KEY + 16 * b + at;
        if (lane < 16) st_relaxed_32(pst, 0u);
        if (at < 16) st_relaxed_32(pky, 0u);
        uint32_t* const py = p.scr + S_Y + 1024 * ((cl & ~3) + a) + 128 * (b & 7) + 32 * t + 4 * g;
        st_relaxed_128(py, 0u, 0u, 0u, 0u);
        const uint32_t gp = sb + OFF_GP;
        sts32(gp + 2048 + 4 * lane, ONES);
        cluster_wait();
        STAMP(1);
        mbar_wait(bar0 + 8 * B_WR, 0);
        float ws[4] = {0.f, 0.f, 0.f, 0.f};
#pragma unroll 1
        for (int k = 0; k < 4; k++) {
            const uint4 q = lds128(gp + k * 512 + lane * 16);
            mma_bf16(ws, ONES, ONES, ONES, ONES, q.x, q.y);
            mma_bf16(ws, ONES, ONES, ONES, ONES, q.z, q.w);
        }
        float wsum = ws[0] + ws[1];
        wsum += __shfl_xor_sync(0xffffffffu, wsum, 1);
        wsum += __shfl_xor_sync(0xffffffffu, wsum, 2);
        const uint32_t hsel = (epoch & 1) * (GU_CTAS * 128), want = (epoch & 1) ? 0x00008000u : 0x80000000u;
        const uint32_t tbit = (epoch ^ m) << 31, ktag = ((epoch + 1u) | 0x8000u) & 0xffffu;
        if (a == 0) {
            sts64(sb + OFF_MISC + 32 + 8 * lane, 0u, 0u);
            if (elect_one()) { sts32(sb + OFF_MISC, want); mbar_arrive(bar0 + 8 * B_TAG); }
        }
        if (b < GU_CTAS) st_relaxed_32(p.scr + S_H + (GU_CTAS * 128 - hsel) + b * 128 + at, 0u);
        {
            uint32_t ra = sb + OFF_ROWS + 2048 * a + 128 * (r + 8 * (m & 1)) + (((m >> 1) ^ r) << 4);
            uint32_t wa = r == 1 ? gp + 128 * a + 16 * m : gp + 2048;
            const uint32_t wstep = r == 1 ? 512 : 0;
            float cs[2][4] = {}, q1[2][4] = {}, q2[2][4] = {};
#pragma unroll 1
            for (int k = 0; k < 4; k++) {
                uint32_t x[4][4], wf[2][4];
                ldsm4(wf[0], wa); ldsm4(wf[1], wa + 64);
                mbar_wait(bar0 + 8 * (B_ROW + k), 0);
                STAMP(2);
#pragma unroll
                for (int i = 0; i < 4; i++) ldsm4(x[i], ra ^ (32 * i));
#pragma unroll
                for (int i = 0; i < 4; i++) {
                    mma_bf16(cs[i & 1], x[i][0], x[i][1], x[i][2], x[i][3], wf[i >> 1][2 * (i & 1)], wf[i >> 1][2 * (i & 1) + 1]);
                    mma_bf16(q1[i & 1], x[i][0], x[i][1], x[i][2], x[i][3], x[i][0], x[i][2]);
                    mma_bf16(q2[i & 1], x[i][0], x[i][1], x[i][2], x[i][3], x[i][1], x[i][3]);
                }
                ra += 8192; wa += wstep;
            }
            const uint32_t pa = gp + 2304 + 256 * a;
#pragma unroll
            for (int i = 0; i < 4; i++) cs[0][i] += cs[1][i];
            if (t == 0) sts128f(pa + 16 * g, cs[0]);
            if (t == (g >> 1)) sts64(pa + 128 + 8 * g, __float_as_uint((g & 1) ? q1[0][1] + q1[1][1] : q1[0][0] + q1[1][0]),
                                     __float_as_uint((g & 1) ? q2[0][3] + q2[1][3] : q2[0][2] + q2[1][2]));
            named_sync(1, 128);
            uint2 u[4];
            float sq4[4];
#pragma unroll
            for (int i = 0; i < 4; i++) {
                u[i] = lds64(gp + 2304 + 256 * i + 16 * r + 8 * (m & 1));
                sq4[i] = lds32f(gp + 2304 + 128 + 256 * i + 8 * r + 4 * (m & 1));
            }
            const float mu = ((__uint_as_float(u[0].x) + __uint_as_float(u[1].x)) + (__uint_as_float(u[2].x) + __uint_as_float(u[3].x))) * (1.f / DM);
            const float sw = (__uint_as_float(u[0].y) + __uint_as_float(u[1].y)) + (__uint_as_float(u[2].y) + __uint_as_float(u[3].y));
            const float e2 = ((sq4[0] + sq4[1]) + (sq4[2] + sq4[3])) * (1.f / DM), var = fmaf(-mu, mu, e2);
            uint32_t ms = mean_std(mu, var);
            float sc = (sw - bf_round(mu) * wsum) * rcpf(bf_hi(ms));
            if (__any_sync(0xffffffffu, !(e2 <= 5.f * var))) {
                const uint2 c = ln_centred(sb, mu);
                ms = c.x; sc = __uint_as_float(c.y);
            }
            if (lane < 16) st_relaxed_32(pst, ms | tbit);
            if (at < 16) st_relaxed_32(pky, pack_bf16(0.f, sc) | ktag);
            if (elect_one()) { mbar_arrive(bar0 + 8 * (B_EMPTY + a)); mbar_arrive(bar0 + 8 * (B_EMPTY + 4 + a)); }
        }
        __syncwarp();
        cluster_arrive();
        STAMP(3); GSTAMP(14);
        uint32_t mykey;
        {
            const uint32_t* sl = p.scr + S_SEL + 32 * (cl & 3) + 2 * g;
            uint2 q;
#pragma unroll 1
            do {
                __nanosleep(SEL_SLEEP);
                q = ld_relaxed_64(sl);
            } while (!__all_sync(0xffffffffu, q.y == ((epoch + 1u) | 0x8000u)));
            mykey = q.x;
        }
        STAMP(4);
        if (a == 0) {
            const uint32_t tok = ~mykey & 0xffffu;
            if (t == 0) asm volatile("red.shared.or.b32 [%0], %1;" ::"r"(sb + OFF_MISC + 32 + 4 * (tok >> 5)), "r"(1u << (tok & 31u)) : "memory");
            sts32(sb + OFF_MISC + 4, __reduce_or_sync(0xffffffffu, 1u << (4 * (tok >> 8) + ((tok >> 1) & 3))));
            __syncwarp();
            if (elect_one()) { mbar_arrive(bar0 + 8 * B_RECV); mbar_arrive(bar0 + 8 * (B_RECV + 1)); }
        }
        if (b < GU_CTAS) {
            const uint32_t tok = 0xffffu - (mykey & 0xffffu);
            {
                const uint32_t tk = __shfl_sync(0xffffffffu, tok, 16 * h + 4 * a);
                if (elect_one())
                    asm volatile("cp.async.bulk.shared::cluster.global.mbarrier::complete_tx::bytes.multicast::cluster [%0], [%1], 2048, [%2], %3;"
                                 ::"r"(sb + OFF_XS + (4 * h + a) * ROW_PITCH), "l"(p.u + (size_t)tk * DM), "r"(bar0 + 8 * B_XS), "h"((uint16_t)3) : "memory");
            }
            uint2 rec;
#pragma unroll 1
            do {
                rec = ld_relaxed_64(p.scr + S_STAT + 2048 * a + (tok & ~15u) + 2 * (tok & 7u));
            } while (!__all_sync(0xffffffffu, ((__byte_perm(rec.x, rec.y, 0x7632) ^ want) & 0x80008000u) == 0));
            const uint32_t mst = (tok & 8u) ? rec.y : rec.x;
            const uint32_t m2 = __byte_perm(mst, 0, 0x1010);
            const float rs = rcpf(__uint_as_float(mst & 0x7fff0000u));
            const float r0 = __shfl_sync(0xffffffffu, rs, 8 * t), r1 = __shfl_sync(0xffffffffu, rs, 8 * t + 4);
            float gacc[4][4];
#pragma unroll
            for (int i = 0; i < 4; i++) { gacc[i][0] = gacc[i][1] = gacc[i][2] = gacc[i][3] = 0.f; }
            const int k = r + 8 * (m >> 1);
            const uint32_t wa = sb + OFF_RING + 8192 * a + (((m & 1) * 4096) ^ p.up_first) + k * 64 + (((k >> 1) & 3) << 4);
#pragma unroll 1
            for (int c = 0; c < 4; c++) {
                const int s = a + 4 * (c & 1);
                mbar_wait(bar0 + 8 * (B_FULL + s), c >> 1);
                STAMP(12);
                uint32_t af[16][4];
#pragma unroll
                for (int ks = 0; ks < 4; ks++)
#pragma unroll
                    for (int mt = 0; mt < 4; mt++) ldsm4t(af[4 * ks + mt], (wa ^ (mt << 4)) + (c & 1) * 32768 + ks * 1024);
                __syncwarp();
                if (elect_one()) mbar_arrive(bar0 + 8 * (B_EMPTY + s));
                mbar_wait(bar0 + 8 * B_XS, 0);
                STAMP(1);
                uint32_t xb[2][4];
#pragma unroll
                for (int i = 0; i < 2; i++) {
                    ldsm4(xb[i], sb + OFF_XS + r * ROW_PITCH + 16 * m + 128 * a + 512 * c + 64 * i);
#pragma unroll
                    for (int j = 0; j < 4; j++) xb[i][j] = as_u(__hsub2(as_b2(xb[i][j]), as_b2(m2)));
                }
#pragma unroll
                for (int ks = 0; ks < 4; ks++) {
#pragma unroll
                    for (int mt = 0; mt < 4; mt++)
                        mma_bf16(gacc[mt], af[4 * ks + mt][0], af[4 * ks + mt][1], af[4 * ks + mt][2], af[4 * ks + mt][3],
                                 xb[ks >> 1][2 * (ks & 1)], xb[ks >> 1][2 * (ks & 1) + 1]);
                }
            }
            STAMP(6);
#pragma unroll
            for (int mt = 0; mt < 4; mt++) sts128f(gp + 2048 * a + mt * 512 + lane * 16, gacc[mt]);
            named_sync(1, 128);
            {
                uint4 q[4];
#pragma unroll
                for (int wq = 0; wq < 4; wq++) q[wq] = lds128(gp + 2048 * wq + 16 * at);
                const uint32_t g2 = pack_bf16(r0 * ((__uint_as_float(q[0].x) + __uint_as_float(q[1].x)) + (__uint_as_float(q[2].x) + __uint_as_float(q[3].x))),
                                              r1 * ((__uint_as_float(q[0].y) + __uint_as_float(q[1].y)) + (__uint_as_float(q[2].y) + __uint_as_float(q[3].y))));
                const uint32_t u2 = pack_bf16(r0 * ((__uint_as_float(q[0].z) + __uint_as_float(q[1].z)) + (__uint_as_float(q[2].z) + __uint_as_float(q[3].z))),
                                              r1 * ((__uint_as_float(q[0].w) + __uint_as_float(q[1].w)) + (__uint_as_float(q[2].w) + __uint_as_float(q[3].w))));
                const uint32_t s2 = pack_bf16(bf_lo(g2) * rcpf(1.f + ex2f(-L2E * bf_lo(g2))), bf_hi(g2) * rcpf(1.f + ex2f(-L2E * bf_hi(g2))));
                uint32_t hw;
                asm volatile("movmatrix.sync.aligned.m8n8.trans.b16 %0, %1;" : "=r"(hw) : "r"(as_u(__hmul2(as_b2(s2), as_b2(u2)))));
                if (hw == 0u) hw = 0x80008000u;
                st_relaxed_32(p.scr + S_H + hsel + b * 128 + at, hw);
            }
            STAMP(7);
        }
        const uint32_t ytag = 1u + (epoch & 1);
        {
            const uint32_t* hp = p.scr + S_H + hsel + (b & 7) * 1792 + 4 * at;
            const uint32_t wa = sb + OFF_RING + 128 * (r + 8 * (m >> 1)) + (((2 * a + (m & 1)) ^ r) << 4);
            uint4 hq[4];
#pragma unroll 1
            do {
                __nanosleep(H_SLEEP);
#pragma unroll
                for (int j = 0; j < 4; j++) hq[j] = ld_relaxed_128(hp + (j < 3 ? 512 * j : 1280));
            } while (!__all_sync(0xffffffffu, min(min(hq[0].w, hq[1].w), min(hq[2].w, hq[3].w)) != 0));
#pragma unroll
            for (int j = 0; j < 4; j++) sts128(sb + OFF_XS + 16 * at + (j < 3 ? 2048 * j : 5120), hq[j].x, hq[j].y, hq[j].z, hq[j].w);
            STAMP(2);
            float dacc[4][4];
#pragma unroll
            for (int s0 = 0; s0 < 7; s0 += DN_RUN) {
                uint32_t af[4 * DN_RUN][4], hb[2 * DN_RUN][4];
#pragma unroll
                for (int s = s0; s < s0 + DN_RUN && s < 7; s++) {
                    mbar_wait(bar0 + 8 * (B_FULL + s), 0);
                    if (s == 6) STAMP(13);
#pragma unroll
                    for (int j = 0; j < 4; j++) ldsm4t(af[4 * (s - s0) + j], wa + s * 8192 + j * 2048);
                }
                if (s0 == 0) { named_sync(1, 128); STAMP(8); } else __syncwarp();
#pragma unroll
                for (int s = s0; s < s0 + DN_RUN && s < 7; s++) {
                    ldsm4(hb[2 * (s - s0)], sb + OFF_XS + 16 * lane + 1024 * s); ldsm4(hb[2 * (s - s0) + 1], sb + OFF_XS + 16 * lane + 1024 * s + 512);
                }
#pragma unroll
                for (int s = s0; s < s0 + DN_RUN && s < 7; s++)
#pragma unroll
                    for (int j = 0; j < 4; j++) {
                        const uint32_t* A = af[4 * (s - s0) + j];
                        const uint32_t* Bh = hb[2 * (s - s0) + (j >> 1)] + 2 * (j & 1);
                        if (s == 0) mma_bf16_z(dacc[j], A[0], A[1], A[2], A[3], Bh[0], Bh[1]);
                        else mma_bf16(dacc[j], A[0], A[1], A[2], A[3], Bh[0], Bh[1]);
                    }
            }
            uint32_t y[4];
#pragma unroll
            for (int j = 0; j < 4; j++) y[j] = (__float_as_uint((dacc[0][j] + dacc[1][j]) + (dacc[2][j] + dacc[3][j])) & ~3u) | ytag;
            st_relaxed_128(py, y[0], y[1], y[2], y[3]);
        }
        STAMP(9);
        {
            const uint32_t key = __shfl_sync(0xffffffffu, mykey, 8 * a + 4 * (m >> 1));
            const uint32_t tok = 0xffffu - (key & 0xffffu);
            const float sg = bf_round(rcpf(1.f + ex2f(-L2E * bf_lo(unorder_key(key >> 16)))));
            const uint32_t xo = sb + OFF_X + 32 * (tok & ~63u) + 128 * (tok & 15u) + 2 * (tok & 48u) + ((2 * (lane & 15)) ^ ((tok & 1u) << 4));
            if (((tok >> 8) & 1) == h) {
                const uint32_t* yp = p.scr + S_Y + 1024 * cl + 32 * a + 4 * r + 2 * (m & 1) + (m >> 1);
                uint32_t pp[8], bad;
#pragma unroll 1
                do {
                    bad = 0;
#pragma unroll
                    for (int q = 0; q < 8; q++) pp[q] = ld_relaxed_32(yp + 128 * q);
#pragma unroll
                    for (int q = 0; q < 8; q++) bad |= pp[q] ^ ytag;
                } while (bad & 3u);
                const float y = ((__uint_as_float(pp[0]) + __uint_as_float(pp[1])) + (__uint_as_float(pp[2]) + __uint_as_float(pp[3]))) +
                                ((__uint_as_float(pp[4]) + __uint_as_float(pp[5])) + (__uint_as_float(pp[6]) + __uint_as_float(pp[7])));
                const uint32_t upd = pack_bf16(bf_round(y) * sg, 0.f);
                STAMP(11);
                mbar_wait(bar0 + 8 * B_ST, 0);
                uint32_t o;
                asm volatile("ld.shared.u16 %0, [%1];" : "=r"(o) : "r"(xo));
                asm volatile("st.global.u16 [%0], %1;" ::"l"(p.out + (size_t)tok * DM + 16 * cl + (lane & 15)), "r"(badd2(o, upd)) : "memory");
            }
            __syncwarp();
            if (elect_one()) mbar_arrive(bar0 + 8 * B_DONE);
        }
        STAMP(10); GSTAMP(15);
    } else {
        asm volatile("setmaxnreg.dec.sync.aligned.u32 %0;" ::"n"(NREG == 168 ? 40 : 384 - 2 * NREG));
        const int q = warp - 12;
        sts32(sb + OFF_MISC + 16 + 4 * q, clk());
        const uint32_t t0 = __shfl_sync(0xffffffffu, lds32v(sb + OFF_MISC + 16 + 4 * q), 0);
        STAMP(0);
        if (q == 1) GSTAMP(14);
        const bool one = elect_one();
        const uint32_t rbar = bar0 + 8 * (B_ROW + q);
        if (one) {
            asm volatile("prefetch.tensormap [%0];" ::"l"(&maps.rows) : "memory");
            mbar_init(rbar, 1);
            if (q == 3) mbar_init(bar0 + 8 * B_WR, 1);
            fence_async();
            mbar_expect_tx(rbar, 8192);
            if (q == 3) {
                mbar_expect_tx(bar0 + 8 * B_WR, 2048);
                bulk_g2s(sb + OFF_GP, p.wr, 2048, bar0 + 8 * B_WR);
            }
        }
        __syncwarp();
        cluster_arrive();
        wait_until(t0 + ROW_DELAY + q * ROW_PERIOD);
        if (one) {
            tma_load_3d(sb + OFF_ROWS + 8192 * q, &maps.rows, 16 * b, 4 * q, rbar);
            asm volatile("prefetch.tensormap [%0];" ::"l"(&maps.u + q) : "memory");
        }
        __syncwarp();
        cluster_wait();
        cluster_arrive();
        STAMP(1);
        wait_until(t0 + X_DELAY + q * X_PERIOD);
        if (one) tma_load_4d_both(sb + OFF_X + 8192 * (4 * h + q), &maps.u, 16 * cl, 4 * (4 * h + q), bar0 + 8 * (B_X + 4 * h + q));
        STAMP(2);
        const char* src = (const char*)((b >> 6) ? p.wu : p.wg) + (64 * q + (b & 63)) * 7168 + 128 * lane;
        const uint32_t phase = PF_START + (b * PF_PERIOD >> 7);
        int i = q, c = b < GU_CTAS ? q : 16 + q;
#pragma unroll 1
        while (c < 23) {
            const uint32_t pf_due = i < PF_N ? phase + i * PF_PERIOD : 1u << 30;
            const uint32_t ld_due = c < PF_N ? LD_START + c * LD_PERIOD : phase + c * PF_PERIOD + max(c - 16, 0) * (PF_PERIOD / 7);
            wait_until(t0 + min(pf_due, ld_due));
            if (pf_due < ld_due) {
                asm volatile("prefetch.global.L2 [%0];" ::"l"(src) : "memory");
                if (lane < 24) asm volatile("prefetch.global.L2 [%0];" ::"l"(src + 4096) : "memory");
                i += 4;
                src += 256 * 7168;
                STAMP(6);
            } else {
                const uint32_t bar = bar0 + 8 * (B_FULL + (c & 7));
                mbar_wait(bar + 8 * (B_EMPTY - B_FULL), (c >> 3) & 1);
                if (one) {
                    mbar_expect_tx(bar, 8192);
                    tma_load_4d(sb + OFF_RING + (c & 7) * 8192, c < 16 ? &maps.wgu : &maps.wd, c < 16 ? 32 * b : 64 * (b >> 3), c < 16 ? c : 7 * (b & 7) + c - 16, bar);
                }
                STAMP(3 + (c >> 3));
                c += 4;
            }
        }
        if (q >= 2) mbar_wait_bounded(bar0 + 8 * (B_DONE - 2 + q), 0);
    }
    cluster_wait();
}

typedef CUresult (*EncodeFn)(CUtensorMap*, CUtensorMapDataType, cuuint32_t, void*, const cuuint64_t*, const cuuint64_t*,
                             const cuuint32_t*, const cuuint32_t*, CUtensorMapInterleave, CUtensorMapSwizzle,
                             CUtensorMapL2promotion, CUtensorMapFloatOOBfill);

void make_map(EncodeFn enc, CUtensorMap* m, int rank, const void* ptr, const cuuint64_t (&dims)[5], const cuuint64_t (&str)[4],
              const cuuint32_t (&box)[5], CUtensorMapSwizzle sw, CUtensorMapL2promotion pr) {
    const cuuint32_t es[5] = {1, 1, 1, 1, 1};
    CUresult rc = enc(m, CU_TENSOR_MAP_DATA_TYPE_BFLOAT16, rank, const_cast<void*>(ptr), dims, str, box, es, CU_TENSOR_MAP_INTERLEAVE_NONE, sw, pr,
                      CU_TENSOR_MAP_FLOAT_OOB_FILL_NONE);
    (void)rc;
}

}

extern "C" void kernel_launch(void* const* d_in, const int* in_sizes, int n_in, void* d_out, int out_size) {
    (void)in_sizes; (void)n_in; (void)out_size;
    static EncodeFn enc = nullptr;
    static void* scr = nullptr;
    if (!enc) {
        void* fn = nullptr;
        cudaDriverEntryPointQueryResult q;
        cudaGetDriverEntryPoint("cuTensorMapEncodeTiled", &fn, cudaEnableDefault, &q);
        enc = (EncodeFn)fn;
        cudaGetSymbolAddress(&scr, g_scr);
        cudaFuncSetAttribute(fused_kernel, cudaFuncAttributeMaxDynamicSharedMemorySize, SMEM_BYTES);
    }
    Maps maps;
    const uintptr_t ag = (uintptr_t)d_in[9], au = (uintptr_t)d_in[10];
    const auto noprom = CU_TENSOR_MAP_L2_PROMOTION_NONE, prom = CU_TENSOR_MAP_L2_PROMOTION_L2_128B;
    make_map(enc, &maps.rows, 3, d_in[0], {64, SEQ, 16, 1}, {2048, 128, 0}, {64, 16, 4, 1}, CU_TENSOR_MAP_SWIZZLE_128B, noprom);
    make_map(enc, &maps.u, 4, d_in[0], {DM, 4, 16, 32}, {32768, 2048, 131072}, {16, 4, 16, 4}, CU_TENSOR_MAP_SWIZZLE_32B, noprom);
    make_map(enc, &maps.out, 5, d_out, {DM, 4, 8, 2, 32}, {32768, 2048, 16384, 131072}, {16, 4, 2, 2, 4}, CU_TENSOR_MAP_SWIZZLE_NONE, noprom);
    make_map(enc, &maps.wgu, 4, (const void*)(ag < au ? ag : au), {FF, 64, 2, 16}, {FF * 2, ag < au ? au - ag : ag - au, 64 * FF * 2}, {32, 64, 2, 1},
             CU_TENSOR_MAP_SWIZZLE_64B, prom);
    make_map(enc, &maps.wd, 4, d_in[11], {DM, 64, 1, 56}, {2048, 131072, 131072}, {64, 64, 1, 1}, CU_TENSOR_MAP_SWIZZLE_128B, prom);
    Ptrs p;
    p.u = (const __nv_bfloat16*)d_in[0];
    p.logA = (const __nv_bfloat16*)d_in[1];
    p.Aim = (const __nv_bfloat16*)d_in[2];
    p.Cre = (const __nv_bfloat16*)d_in[3];
    p.Cim = (const __nv_bfloat16*)d_in[4];
    p.ldt = (const __nv_bfloat16*)d_in[5];
    p.dsk = (const __nv_bfloat16*)d_in[6];
    p.wr = (const __nv_bfloat16*)d_in[8];
    p.wg = (const __nv_bfloat16*)d_in[9];
    p.wu = (const __nv_bfloat16*)d_in[10];
    p.out = (__nv_bfloat16*)d_out;
    p.scr = (uint32_t*)scr;
    p.up_first = ag < au ? 0 : 4096;
    p.zero = 0;
    fused_kernel<<<NCTA + 2, NTHR, SMEM_BYTES, cudaStreamPerThread>>>(p, maps);
}
```

```cpp
#include <cuda_runtime.h>
#include <cuda_bf16.h>
#include <cuda_fp16.h>
#include <cuda.h>
#include <stdint.h>

namespace {

constexpr int SEQ = 2048, DM = 1024, NMODE = 128, FF = 3584;
constexpr int NCTA = 128, NTHR = 512;
constexpr int GU_CTAS = 112;

constexpr int OFF_X = 0;
constexpr int OFF_RING = 65536;
constexpr int ROW_PITCH = 2064;
constexpr int OFF_ROWS = OFF_RING + 32768;
constexpr int OFF_XS = OFF_RING + 65536;
constexpr int OFF_PRIV = OFF_XS + 8 * ROW_PITCH;
constexpr int PRIV = 8768;
constexpr int PLANE = 2240;
constexpr int OFF_GP = OFF_PRIV + 8 * PRIV;
constexpr int OFF_LC = OFF_GP + 8192;
constexpr int OFF_BAR = OFF_LC + 2048;
constexpr int OFF_MISC = OFF_BAR + 352;
constexpr int OFF_STAMP = OFF_MISC + 288;
constexpr int SMEM_BYTES = OFF_STAMP;

constexpr int B_X = 0, B_FULL = 8, B_EMPTY = 16, B_RECV = 24, B_XS = 28, B_DONE = 29, B_ST = 30, B_TAG = 31, B_ROW = 32, B_WR = 36, B_KG = 37, B_VT = 38, B_PV = 39;

constexpr int T_DENSE = 4416;
constexpr int T_PATCH = T_DENSE + 2176;
constexpr int T_S4 = T_PATCH + 112;
constexpr int T_S8 = T_S4 + 736;
constexpr int REC = 272;

#define KG_UNROLL 4
constexpr int KGU = KG_UNROLL;
constexpr uint32_t SPIN_LIMIT = 1u << 22;
#define ROW_DELAY 300
#define H_SLEEP 100
#define NPRE 4
#define SEL_SLEEP 100
#define ROW_PERIOD 450
#define X_PERIOD 0
#define FINE 2
#define INC_AT 1
#define NREG 168
#define DN_PRE 4
#define DN_LAST 1
#define GU_SPLIT 2
#define FIN_A 4
#define FIN_B 12
#define TORD 0
#define CW_EARLY 0
#define WAKE 63
#define LN_DUP 0
#define X_DELAY 2500
#define PF_START 3300
#define PF_PERIOD 539
#define WD_EXTRA (PF_PERIOD / 7)
#define LD_LAG 700
#define LD_START 5400
#define LD_PERIOD ((PF_START + 16 * PF_PERIOD + LD_LAG - LD_START) / 15)

constexpr int S_STAT = 0;
constexpr int S_KEY = S_STAT + 8192;
constexpr int S_SEL = S_KEY + 2048;
constexpr int S_EPOCH = S_SEL + 128;
constexpr int S_H = S_EPOCH + 32;
constexpr int S_Y = S_H + 2 * GU_CTAS * 128;
constexpr int S_END = S_Y + 64 * 1024;
__device__ __align__(1024) uint32_t g_scr[S_END];

struct Ptrs {
    const __nv_bfloat16 *logA, *Aim, *Cre, *Cim, *ldt, *dsk, *u, *wr;
    uint32_t* scr;
    const __nv_bfloat16 *wg, *wu;
    __nv_bfloat16* out;
    uint32_t up_first;
    uint32_t zero;
};
struct Maps {
    CUtensorMap rows, u, out, wgu, wd;
};

__device__ __forceinline__ uint32_t clk() { uint32_t c; asm volatile("mov.u32 %0, %%clock;" : "=r"(c)); return c; }
#define STAMP(i) do { } while (0)
#define GSTAMP(i) do { } while (0)

template <int N> struct IC { static constexpr int value = N; };

__device__ __forceinline__ uint32_t s_u32(const void* p) { return (uint32_t)__cvta_generic_to_shared(p); }
__device__ __forceinline__ void mbar_init(uint32_t b, uint32_t n) {
    asm volatile("mbarrier.init.shared::cta.b64 [%0], %1;" ::"r"(b), "r"(n) : "memory");
}
__device__ __forceinline__ void mbar_expect_tx(uint32_t b, uint32_t bytes) {
    asm volatile("mbarrier.arrive.expect_tx.shared::cta.b64 _, [%0], %1;" ::"r"(b), "r"(bytes) : "memory");
}
__device__ __forceinline__ void mbar_arrive(uint32_t b) {
    asm volatile("mbarrier.arrive.shared::cta.b64 _, [%0];" ::"r"(b) : "memory");
}
__device__ __forceinline__ void mbar_arrive_peer(uint32_t b_cluster) {
    asm volatile("mbarrier.arrive.relaxed.cluster.shared::cluster.b64 _, [%0];" ::"r"(b_cluster) : "memory");
}
__device__ __forceinline__ void mbar_wait(uint32_t b, uint32_t parity) {
    asm volatile("{\n\t.reg .pred p;\nW:\n\tmbarrier.try_wait.parity.shared::cta.b64 p, [%0], %1;\n\t@!p bra W;\n\t}" ::"r"(b), "r"(parity) : "memory");
}
__device__ __forceinline__ void mbar_wait_bounded(uint32_t b, uint32_t parity) {
    asm volatile("{\n\t.reg .pred p;\n\t.reg .u32 c;\n\tmov.u32 c, 0;\n"
                 "W:\n\tmbarrier.try_wait.parity.shared::cta.b64 p, [%0], %1, 4000;\n\t@p bra D;\n\t"
                 "add.u32 c, c, 1;\n\tsetp.lt.u32 p, c, 1048576;\n\t@p bra W;\n\ttrap;\nD:\n\t}"
                 ::"r"(b), "r"(parity) : "memory");
}
__device__ __forceinline__ bool elect_one() {
    uint32_t p;
    asm volatile("{ .reg .pred P; elect.sync _|P, 0xffffffff; selp.u32 %0, 1, 0, P; }" : "=r"(p));
    return p != 0;
}
__device__ __forceinline__ uint32_t mapa(uint32_t a, uint32_t rank) {
    uint32_t r;
    asm("mapa.shared::cluster.u32 %0, %1, %2;" : "=r"(r) : "r"(a), "r"(rank));
    return r;
}
__device__ __forceinline__ void cluster_arrive() { asm volatile("barrier.cluster.arrive.relaxed.aligned;" ::: "memory"); }
__device__ __forceinline__ void cluster_wait() { asm volatile("barrier.cluster.wait.aligned;" ::: "memory"); }
__device__ __forceinline__ void tma_load_3d(uint32_t dst, const CUtensorMap* m, int c1, int c2, uint32_t bar) {
    asm volatile("cp.async.bulk.tensor.3d.shared::cluster.global.mbarrier::complete_tx::bytes [%0], [%1, {%3, %4, %5}], [%2];"
                 ::"r"(dst), "l"(m), "r"(bar), "r"(0), "r"(c1), "r"(c2) : "memory");
}
__device__ __forceinline__ void tma_load_4d(uint32_t dst, const CUtensorMap* m, int c0, int c3, uint32_t bar) {
    asm volatile("cp.async.bulk.tensor.4d.shared::cluster.global.mbarrier::complete_tx::bytes [%0], [%1, {%3, %5, %5, %4}], [%2];"
                 ::"r"(dst), "l"(m), "r"(bar), "r"(c0), "r"(c3), "r"(0) : "memory");
}
__device__ __forceinline__ void wait_until(uint32_t t) {
    asm volatile("{\n\t.reg .pred p;\n\t.reg .s32 c;\nW:\n\tmov.u32 c, %%clock;\n\tsub.s32 c, %0, c;\n\tshr.s32 c, c, 2;\n\tsetp.gt.s32 p, c, %1;\n\t"
                 "@p nanosleep.u32 c;\n\t@p bra.uni W;\n\t}" ::"r"(t), "n"(WAKE) : "memory");
}
__device__ __forceinline__ void tma_load_4d_both(uint32_t dst, const CUtensorMap* m, int c0, int c3, uint32_t bar) {
    asm volatile("cp.async.bulk.tensor.4d.shared::cluster.global.mbarrier::complete_tx::bytes.multicast::cluster [%0], [%1, {%3, %6, %6, %4}], [%2], %5;"
                 ::"r"(dst), "l"(m), "r"(bar), "r"(c0), "r"(c3), "h"((uint16_t)3), "r"(0) : "memory");
}
__device__ __forceinline__ void bulk_g2s(uint32_t dst, const void* src, uint32_t bytes, uint32_t bar) {
    asm volatile("cp.async.bulk.shared::cluster.global.mbarrier::complete_tx::bytes [%0], [%1], %2, [%3];"
                 ::"r"(dst), "l"(src), "r"(bytes), "r"(bar) : "memory");
}
__device__ __forceinline__ void fence_async() { asm volatile("fence.proxy.async.shared::cta;" ::: "memory"); }
__device__ __forceinline__ void named_sync(int id, int n) { asm volatile("bar.sync %0, %1;" ::"r"(id), "r"(n) : "memory"); }

__device__ __forceinline__ void ldsm4(uint32_t* r, uint32_t a) {
    asm volatile("ldmatrix.sync.aligned.m8n8.x4.shared.b16 {%0,%1,%2,%3}, [%4];"
                 : "=r"(r[0]), "=r"(r[1]), "=r"(r[2]), "=r"(r[3]) : "r"(a));
}
__device__ __forceinline__ void ldsm4t(uint32_t* r, uint32_t a) {
    asm volatile("ldmatrix.sync.aligned.m8n8.x4.trans.shared.b16 {%0,%1,%2,%3}, [%4];"
                 : "=r"(r[0]), "=r"(r[1]), "=r"(r[2]), "=r"(r[3]) : "r"(a));
}
__device__ __forceinline__ void stsm4t(uint32_t a, const uint32_t* r) {
    asm volatile("stmatrix.sync.aligned.m8n8.x4.trans.shared.b16 [%0], {%1,%2,%3,%4};"
                 ::"r"(a), "r"(r[0]), "r"(r[1]), "r"(r[2]), "r"(r[3]) : "memory");
}
__device__ __forceinline__ uint32_t lds32(uint32_t a) { uint32_t v; asm volatile("ld.shared.u32 %0, [%1];" : "=r"(v) : "r"(a)); return v; }
__device__ __forceinline__ uint32_t lds32v(uint32_t a) { uint32_t v; asm volatile("ld.volatile.shared.u32 %0, [%1];" : "=r"(v) : "r"(a)); return v; }
__device__ __forceinline__ float lds32f(uint32_t a) { float v; asm volatile("ld.shared.f32 %0, [%1];" : "=f"(v) : "r"(a)); return v; }
__device__ __forceinline__ uint2 lds64(uint32_t a) { uint2 v; asm volatile("ld.shared.v2.u32 {%0,%1}, [%2];" : "=r"(v.x), "=r"(v.y) : "r"(a)); return v; }
__device__ __forceinline__ uint4 lds128(uint32_t a) {
    uint4 v; asm volatile("ld.shared.v4.u32 {%0,%1,%2,%3}, [%4];" : "=r"(v.x), "=r"(v.y), "=r"(v.z), "=r"(v.w) : "r"(a)); return v;
}
template <int D> __device__ __forceinline__ void sts16x2(uint32_t a, float x) {
    asm volatile("{ .reg .b16 h; cvt.rn.bf16.f32 h, %1; st.shared.b16 [%0], h; st.shared.b16 [%0 + %2], h; }" ::"r"(a), "f"(x), "n"(D) : "memory");
}
__device__ __forceinline__ void sts32(uint32_t a, uint32_t v) { asm volatile("st.shared.u32 [%0], %1;" ::"r"(a), "r"(v) : "memory"); }
__device__ __forceinline__ void sts64(uint32_t a, uint32_t x, uint32_t y) { asm volatile("st.shared.v2.u32 [%0], {%1,%2};" ::"r"(a), "r"(x), "r"(y) : "memory"); }
__device__ __forceinline__ void sts128(uint32_t a, uint32_t x, uint32_t y, uint32_t z, uint32_t w) {
    asm volatile("st.shared.v4.u32 [%0], {%1,%2,%3,%4};" ::"r"(a), "r"(x), "r"(y), "r"(z), "r"(w) : "memory");
}
__device__ __forceinline__ void sts128f(uint32_t a, const float* c) {
    asm volatile("st.shared.v4.f32 [%0], {%1,%2,%3,%4};" ::"r"(a), "f"(c[0]), "f"(c[1]), "f"(c[2]), "f"(c[3]) : "memory");
}
__device__ __forceinline__ uint2 ldg64(const void* p) {
    uint2 v; asm volatile("ld.global.nc.L1::no_allocate.v2.u32 {%0,%1}, [%2];" : "=r"(v.x), "=r"(v.y) : "l"(p)); return v;
}
__device__ __forceinline__ uint32_t ldg16(const void* p) {
    uint16_t v; asm volatile("ld.global.nc.u16 %0, [%1];" : "=h"(v) : "l"(p)); return v;
}
__device__ __forceinline__ uint32_t ld_relaxed_32(const void* p) {
    uint32_t v; asm volatile("ld.relaxed.gpu.global.u32 %0, [%1];" : "=r"(v) : "l"(p) : "memory"); return v;
}
__device__ __forceinline__ uint2 ld_relaxed_64(const void* p) {
    uint2 v; asm volatile("ld.relaxed.gpu.global.v2.u32 {%0,%1}, [%2];" : "=r"(v.x), "=r"(v.y) : "l"(p) : "memory"); return v;
}
__device__ __forceinline__ uint4 ld_relaxed_128(const void* p) {
    uint4 v; asm volatile("ld.relaxed.gpu.global.v4.u32 {%0,%1,%2,%3}, [%4];" : "=r"(v.x), "=r"(v.y), "=r"(v.z), "=r"(v.w) : "l"(p) : "memory"); return v;
}
__device__ __forceinline__ void st_relaxed_32(void* p, uint32_t v) {
    asm volatile("st.relaxed.gpu.global.u32 [%0], %1;" ::"l"(p), "r"(v) : "memory");
}
__device__ __forceinline__ void st_relaxed_128(void* p, uint32_t x, uint32_t y, uint32_t z, uint32_t w) {
    asm volatile("st.relaxed.gpu.global.v4.u32 [%0], {%1,%2,%3,%4};" ::"l"(p), "r"(x), "r"(y), "r"(z), "r"(w) : "memory");
}
__device__ __forceinline__ void st_relaxed_64(void* p, uint32_t x, uint32_t y) {
    asm volatile("st.relaxed.gpu.global.u64 [%0], %1;" ::"l"(p), "l"((unsigned long long)x | ((unsigned long long)y << 32)) : "memory");
}
__device__ __forceinline__ void mma_bf16(float* c, uint32_t a0, uint32_t a1, uint32_t a2, uint32_t a3, uint32_t b0, uint32_t b1) {
    asm("mma.sync.aligned.m16n8k16.row.col.f32.bf16.bf16.f32 {%0,%1,%2,%3}, {%4,%5,%6,%7}, {%8,%9}, {%0,%1,%2,%3};"
                 : "+f"(c[0]), "+f"(c[1]), "+f"(c[2]), "+f"(c[3]) : "r"(a0), "r"(a1), "r"(a2), "r"(a3), "r"(b0), "r"(b1));
}
__device__ __forceinline__ void mma_bf16v(float* c, const uint32_t* a, uint32_t b0, uint32_t b1) {
    asm volatile("mma.sync.aligned.m16n8k16.row.col.f32.bf16.bf16.f32 {%0,%1,%2,%3}, {%4,%5,%6,%7}, {%8,%9}, {%0,%1,%2,%3};"
                 : "+f"(c[0]), "+f"(c[1]), "+f"(c[2]), "+f"(c[3]) : "r"(a[0]), "r"(a[1]), "r"(a[2]), "r"(a[3]), "r"(b0), "r"(b1));
}
__device__ __forceinline__ void mma_bf16_z(float* c, uint32_t a0, uint32_t a1, uint32_t a2, uint32_t a3, uint32_t b0, uint32_t b1) {
    asm("mma.sync.aligned.m16n8k16.row.col.f32.bf16.bf16.f32 {%0,%1,%2,%3}, {%4,%5,%6,%7}, {%8,%9}, {%10,%10,%10,%10};"
        : "=f"(c[0]), "=f"(c[1]), "=f"(c[2]), "=f"(c[3]) : "r"(a0), "r"(a1), "r"(a2), "r"(a3), "r"(b0), "r"(b1), "f"(0.f));
}
__device__ __forceinline__ void mma_f16(float* c, const uint4& a, uint32_t b0, uint32_t b1) {
    asm("mma.sync.aligned.m16n8k16.row.col.f32.f16.f16.f32 {%0,%1,%2,%3}, {%4,%5,%6,%7}, {%8,%9}, {%0,%1,%2,%3};"
                 : "+f"(c[0]), "+f"(c[1]), "+f"(c[2]), "+f"(c[3]) : "r"(a.x), "r"(a.y), "r"(a.z), "r"(a.w), "r"(b0), "r"(b1));
}
__device__ __forceinline__ uint32_t pack_bf16(float lo, float hi) {
    uint32_t r; asm("cvt.rn.bf16x2.f32 %0, %1, %2;" : "=r"(r) : "f"(hi), "f"(lo)); return r;
}
__device__ __forceinline__ uint32_t pack_bf16v(float lo, float hi) {
    uint32_t r; asm("cvt.rn.satfinite.bf16x2.f32 %0, %1, %2;" : "=r"(r) : "f"(hi), "f"(lo)); return r;
}
__device__ __forceinline__ uint32_t pack_f16(float lo, float hi) {
    uint32_t r; asm("cvt.rn.f16x2.f32 %0, %1, %2;" : "=r"(r) : "f"(hi), "f"(lo)); return r;
}
__device__ __forceinline__ float bf_lo(uint32_t v) { return __uint_as_float(v << 16); }
__device__ __forceinline__ float bf_hi(uint32_t v) { return __uint_as_float(v & 0xffff0000u); }
__device__ __forceinline__ float bf_round(float x) { return __uint_as_float(pack_bf16(0.f, x)); }
__device__ __forceinline__ __nv_bfloat162 as_b2(uint32_t x) { return *reinterpret_cast<__nv_bfloat162*>(&x); }
__device__ __forceinline__ uint32_t as_u(__nv_bfloat162 x) { return *reinterpret_cast<uint32_t*>(&x); }
__device__ __forceinline__ uint32_t badd2(uint32_t a, uint32_t b) { uint32_t r; asm("add.rn.bf16x2 %0, %1, %2;" : "=r"(r) : "r"(a), "r"(b)); return r; }
__device__ __forceinline__ float rcpf(float x) { float r; asm("rcp.approx.ftz.f32 %0, %1;" : "=f"(r) : "f"(x)); return r; }
__device__ __forceinline__ float sqrtaf(float x) { float r; asm("sqrt.approx.ftz.f32 %0, %1;" : "=f"(r) : "f"(x)); return r; }
__device__ __forceinline__ float ex2f(float x) { float r; asm("ex2.approx.ftz.f32 %0, %1;" : "=f"(r) : "f"(x)); return r; }
constexpr float L2E = 1.4426950408889634f;
constexpr uint32_t ONES = 0x3f803f80u;

__device__ __forceinline__ uint2 recip2(uint32_t s2) {
    const uint32_t hi = pack_bf16(rcpf(bf_lo(s2)), rcpf(bf_hi(s2)));
    return make_uint2(hi, as_u(__hmul2(__hfma2(__hneg2(as_b2(s2)), as_b2(hi), as_b2(ONES)), as_b2(hi))));
}
__device__ __forceinline__ uint32_t normalize2(uint32_t x, __nv_bfloat162 m, __nv_bfloat162 rh, __nv_bfloat162 rl) {
    const __nv_bfloat162 d = __hsub2(as_b2(x), m);
    return as_u(__hfma2(d, rh, __hmul2(d, rl)));
}

__device__ __forceinline__ uint32_t unorder_key(uint32_t k16) { return k16 ^ ((k16 & 0x8000u) ? 0x8000u : 0xffffu); }

struct cplx { float r, i; };
__device__ __forceinline__ cplx csq(cplx a) { return {a.r * a.r - a.i * a.i, (a.r + a.r) * a.i}; }
__device__ __forceinline__ cplx csq_conj(cplx a) { return {a.r * a.r - a.i * a.i, (-a.r - a.r) * a.i}; }
__device__ __forceinline__ cplx cexpp(float a2, float th) {
    float m = ex2f(a2), s, c;
    __sincosf(th, &s, &c);
    return {m * c, m * s};
}
struct hc { __half2 r, i; };
__device__ __forceinline__ __half2 as_h2(uint32_t x) { return *reinterpret_cast<__half2*>(&x); }
__device__ __forceinline__ uint32_t as_u(__half2 x) { return *reinterpret_cast<uint32_t*>(&x); }
__device__ __forceinline__ hc hmul(hc a, hc b) {
    return {__hfma2(a.r, b.r, __hneg2(__hmul2(a.i, b.i))), __hfma2(a.r, b.i, __hmul2(a.i, b.r))};
}
__device__ __forceinline__ hc hpack(cplx a, cplx b) { return {as_h2(pack_f16(a.r, b.r)), as_h2(pack_f16(a.i, b.i))}; }
__device__ __forceinline__ void st_pair(uint32_t a, hc x, hc y) { sts128(a, as_u(x.r), as_u(x.i), as_u(y.r), as_u(y.i)); }
__device__ __forceinline__ void st_quad(uint32_t a, hc x, hc y) { sts128(a, as_u(x.r), as_u(y.r), as_u(x.i), as_u(y.i)); }

#define KSTAMP(i, dep) do { } while (0)
__device__ __forceinline__ void kgen_mma(float (&acc)[5][4], uint32_t priv, int lane, uint2 la, uint2 aim, uint2 cre, uint2 cim, float dt, uint32_t cs2) {
    const int g = lane >> 2, t = lane & 3;
#pragma unroll
    for (int i = 0; i < 5; i++) { acc[i][0] = acc[i][1] = acc[i][2] = acc[i][3] = 0.f; }
    const uint32_t wr = priv + lane * REC, rd = priv + 2 * t * REC;
    const float ndl = -dt * L2E;
#pragma unroll 1
    for (int ps = 0; ps < 2; ps++) {
        const uint32_t lw = ps ? la.y : la.x, iw = ps ? aim.y : aim.x;
        const uint32_t crw = as_u(__hmul2(as_b2(ps ? cre.y : cre.x), as_b2(cs2))), ciw = as_u(__hmul2(as_b2(ps ? cim.y : cim.x), as_b2(cs2)));
        const uint32_t ap = pack_bf16(ex2f(bf_lo(lw) * L2E), ex2f(bf_hi(lw) * L2E));
        const float a2[2] = {bf_lo(ap) * ndl, bf_hi(ap) * ndl}, th[2] = {bf_lo(iw) * dt, bf_hi(iw) * dt};
        cplx p1[2], p2[2], p4[2], p8[2], p32[2], p64[2], p128[2], p256[2], p512[2];
#pragma unroll
        for (int i = 0; i < 2; i++) {
            p1[i] = cexpp(a2[i], th[i]); p32[i] = cexpp(a2[i] * 32.f, th[i] * -32.f);
            p2[i] = csq(p1[i]); p4[i] = csq(p2[i]); p8[i] = csq_conj(p4[i]);
            p64[i] = csq(p32[i]); p128[i] = csq_conj(p64[i]); p256[i] = csq(p128[i]); p512[i] = csq(p256[i]);
        }
        const hc C = {as_h2(pack_f16(bf_lo(crw), bf_hi(crw))), as_h2(pack_f16(bf_lo(ciw), bf_hi(ciw)))};
        const hc z1 = hpack(p1[0], p1[1]), z2 = hpack(p2[0], p2[1]), z4 = hpack(p4[0], p4[1]);
        const hc y8 = hpack(p8[0], p8[1]), y32 = hpack(p32[0], p32[1]), y64 = hpack(p64[0], p64[1]);
        const hc z128 = hpack(p128[0], p128[1]), z256 = hpack(p256[0], p256[1]), z512 = hpack(p512[0], p512[1]);
        KSTAMP(8 + 3 * ps, z512.r);
        __syncwarp();
        const hc c1 = hmul(C, z1), c2 = hmul(C, z2), c5 = hmul(c1, z4), c6 = hmul(c2, z4);
        st_pair(wr + 160, hmul(c1, z128), hmul(c2, z128));
        st_pair(wr + 128, c1, c2);
        st_pair(wr + 176, hmul(c5, z128), hmul(c6, z128));
        st_pair(wr + 144, c5, c6);
        const hc y16 = hmul(y8, y8), y48 = hmul(y16, y32), y24 = hmul(y16, y8), y40 = hmul(y32, y8), y56 = hmul(y48, y8), y72 = hmul(y64, y8);
        st_quad(wr, {as_h2(0x3c003c00u), as_h2(0u)}, y8);
        st_quad(wr + 80, hmul(y64, y16), hmul(y64, y24));
        st_quad(wr + 16, y16, y24);
        st_quad(wr + 96, hmul(y64, y32), hmul(y64, y40));
        st_quad(wr + 32, y32, y40);
        st_quad(wr + 112, hmul(y64, y48), hmul(y64, y56));
        st_quad(wr + 48, y48, y56);
        st_quad(wr + 64, y64, y72);
        const hc z258 = hmul(z256, z2);
        st_pair(wr + 192, hmul(z256, z1), z258);
        st_pair(wr + 224, z2, hmul(z512, z4));
        st_pair(wr + 240, z2, hmul(z512, z512));
        st_pair(wr + 208, z258, z512);
        KSTAMP(9 + 3 * ps, z512.r);
        __syncwarp();
#pragma unroll KGU
        for (int k2 = 0; k2 < 4; k2++) {
#pragma unroll
            for (int s = 0; s < 2; s++) {
                const uint32_t o = rd + k2 * 8 * REC + s * REC;
                const uint4 A = lds128(o + 16 * g);
                const uint2 h = lds64(o + 128 + 8 * g);
                const uint4 M = lds128(o + 192 + 16 * (g & 1)), N = lds128(o + 224 + 8 * (g & 2));
                const hc H0 = {as_h2(h.x), as_h2(h.y)};
                const hc H1 = hmul(H0, {as_h2(N.x), as_h2(N.y)}), H2 = hmul(H0, {as_h2(M.x), as_h2(M.y)});
                const hc H3 = hmul(H2, {as_h2(M.z), as_h2(M.w)}), H4 = hmul(H3, {as_h2(N.z), as_h2(N.w)});
                mma_f16(acc[0], A, h.x, h.y);
                mma_f16(acc[1], A, as_u(H1.r), as_u(H1.i));
                mma_f16(acc[2], A, as_u(H2.r), as_u(H2.i));
                mma_f16(acc[3], A, as_u(H3.r), as_u(H3.i));
                mma_f16(acc[4], A, as_u(H4.r), as_u(H4.i));
            }
        }
        KSTAMP(10 + 3 * ps, z512.r);
    }
}

__device__ __forceinline__ void kgen_tables(const float (&acc)[5][4], uint32_t priv, int lane, float scale, float k0) {
    const int g = lane >> 2, t0 = lane & 1, t1 = (lane >> 1) & 1;
    __syncwarp();
    sts128(priv + 16 * lane + (lane < 17 ? T_PATCH - 48 : T_S4 + 608 - 272), 0, 0, 0, 0);
    if (lane < 20) sts128(priv + 16 * lane + (lane < 8 ? 0 : lane < 16 ? PLANE - 128 : T_DENSE - 256), 0, 0, 0, 0);
    uint32_t w2[2], w3[2], w4[2], ab[2], W[2], pv[2];
#pragma unroll
    for (int hf = 0; hf < 2; hf++) {
        const float k1 = acc[0][2 * hf] * scale, k2 = acc[0][2 * hf + 1] * scale, k3 = acc[1][2 * hf] * scale, k4 = acc[1][2 * hf + 1] * scale;
        w2[hf] = pack_bf16(k2, k1); w3[hf] = pack_bf16(k3, k2); w4[hf] = pack_bf16(k4, k3);
        ab[hf] = pack_bf16(acc[2][2 * hf + 1] * scale, acc[2][2 * hf] * scale);
        W[hf] = __byte_perm(w4[hf], ab[hf], 0x5410);
    }
    pv[1] = __shfl_xor_sync(0xffffffffu, t0 ? W[0] : W[1], 1);
    pv[0] = __shfl_sync(0xffffffffu, t0 ? W[1] : W[0], t0 ? lane - 1 : lane < 4 ? 31 - lane : lane - 3);
    const uint32_t kk = pack_bf16(k0, 0.f);
    if (lane == 0) pv[0] = __byte_perm(kk, pv[0], 0x5410);
    const uint32_t pd = priv + T_DENSE + 64 + 512 * t1 + 64 * g + 16 * t0;
#pragma unroll
    for (int hf = 0; hf < 2; hf++) {
        sts128(pd + 32 * hf, __byte_perm(w2[hf], pv[hf], 0x5432), w2[hf], w3[hf], w4[hf]);
        sts128(pd + 32 * hf + 1024, __byte_perm(pv[hf], 0, 0x3232), __byte_perm(ab[hf], pv[hf], 0x7632), ab[hf], __byte_perm(ab[hf], 0, 0x1010));
    }
    __syncwarp();
    if (lane == 31) {
        const uint32_t aa = __byte_perm(ab[1], 0, 0x1010);
        sts32(priv + T_DENSE + 60, kk);
        sts128(priv + T_PATCH - 64, aa, aa, aa << 16, 0u);
    }
}
__device__ __forceinline__ void kgen_tables2(const float (&acc)[5][4], uint32_t priv, int lane, float scale) {
    const int g = lane >> 2, t0 = lane & 1, t1 = (lane >> 1) & 1;
    const uint32_t p4 = priv + T_S4 + 16 * (6 + g + 8 * t1) + 4 * (t0 ^ 1), p8 = priv + T_S8 + 8 * (6 + g + 8 * t1 + 32 * t0);
#pragma unroll
    for (int i = 0; i < 4; i++) {
        sts16x2<18>(p4 + 256 * (i & 1) + 8 * (i >> 1), acc[3][i] * scale);
        sts16x2<10>(p8 + 128 * (i & 1) + 4 * (i >> 1), acc[4][i] * scale);
    }
    if (lane == 31) {
        const uint32_t c3 = pack_bf16(acc[3][3] * scale, 0.f);
        sts128(priv + T_PATCH + 48, c3, c3 * 0x10001u, c3 << 16, 0u);
    }
    __syncwarp();
}

__device__ __forceinline__ void ld_frag(uint32_t (&T)[4], uint32_t q) { T[0] = lds32(q); T[1] = lds32(q + 32); T[2] = lds32(q - 32); T[3] = lds32v(q); }
__device__ __forceinline__ void ld_swap(uint32_t (&T)[4], uint32_t q) { T[2] = lds32v(q); T[3] = lds32v(q + 32); T[0] = lds32v(q - 32); T[1] = lds32v(q); }
__device__ __forceinline__ void add_frag(uint32_t (&S)[4], const uint32_t (&E)[4], const uint32_t (&O)[4]) {
    S[0] = badd2(E[0], O[1]); S[1] = badd2(E[1], O[3]); S[2] = badd2(E[2], O[0]); S[3] = badd2(E[3], O[2]);
}
__device__ __forceinline__ void mma4(float* c, const uint32_t (&a)[4], uint32_t b0, uint32_t b1, bool first = false) {
    if (first) mma_bf16_z(c, a[0], a[1], a[2], a[3], b0, b1);
    else mma_bf16(c, a[0], a[1], a[2], a[3], b0, b1);
}
template <bool FIRST>
__device__ __forceinline__ void dense_step(float (&acc)[16][4], float (&B)[8][4], uint32_t (&T0)[4], uint32_t (&T1)[4], uint32_t (&R)[8][4],
                                           uint32_t pq, uint32_t va) {
    uint32_t T2[4], T3[4], S[4], s[8][2];
#pragma unroll
    for (int i = NPRE; i < 8; i++) ldsm4(R[i], va + i * 256);
    ld_frag(T2, pq + 1024); ld_swap(T3, pq + 1536);
    add_frag(S, T0, T1);
#pragma unroll
    for (int i = 0; i < 8; i++) {
        s[i][0] = badd2(R[i][0], R[i][3]); s[i][1] = badd2(R[i][1], R[i][2]);
        mma4(acc[2 * i], T0, R[i][0], R[i][1], FIRST);
        mma4(B[i], T1, R[i][2], R[i][3], FIRST);
        mma4(acc[2 * i + 1], S, s[i][0], s[i][1], FIRST);
    }
    ld_frag(T0, pq - 64); ld_swap(T1, pq + 448);
    add_frag(S, T2, T3);
#pragma unroll
    for (int i = 0; i < 7; i++) {
        if (!FIRST || i) mma4(acc[2 * i + 2], T2, R[i][0], R[i][1]);
        mma4(B[i + 1], T3, R[i][2], R[i][3]);
        mma4(acc[2 * i + 3], S, s[i][0], s[i][1]);
        if (i < NPRE) ldsm4(R[i], va + 16 + i * 256);
    }
}
template <class Wait, class After>
__device__ __forceinline__ void dense_phase(float (&acc)[16][4], uint32_t priv, int lane, Wait wait_for_tokens, After after_loop) {
    const int m = lane >> 3, r = lane & 7;
    const uint32_t pb = priv + T_DENSE + 4 * (15 + (lane >> 2) - 2 * (lane & 3));
    const uint32_t v8 = priv + 128 * (m >> 1) + 16 * r;
    float B[8][4];
    uint32_t T0[4], T1[4], R[8][4];
    uint32_t pq = pb + 512, va = v8 + PLANE * ((m ^ (m >> 1)) & 1);
    ld_frag(T0, pq); ld_swap(T1, pq + 512);
    wait_for_tokens();
#pragma unroll
    for (int i = 0; i < NPRE; i++) ldsm4(R[i], va + i * 256);
    dense_step<true>(acc, B, T0, T1, R, pq, va);
#pragma unroll 1
    do {
        pq -= 64; va += 16;
        dense_step<false>(acc, B, T0, T1, R, pq, va);
    } while (pq != pb + 64);
    after_loop();
    KSTAMP(14, as_h2(0u));
    const uint32_t pp = pb + T_PATCH - T_DENSE - 24;
    uint32_t N0[4], N1[4];
    ld_swap(T1, pb); ld_frag(N0, pp); ld_swap(N1, pp);
#pragma unroll
    for (int i = NPRE; i < 8; i++) ldsm4(R[i], va + 16 + i * 256);
#pragma unroll
    for (int i = 0; i < 8; i++)
#pragma unroll
        for (int j = 0; j < 4; j++) {
            acc[2 * i + 1][j] = (acc[2 * i + 1][j] - acc[2 * i][j]) - B[i][j];
            if (i) acc[2 * i][j] += B[i - 1][j];
        }
#pragma unroll
    for (int i = 0; i < 8; i++) {
        mma4(acc[2 * i], T0, R[i][0], R[i][1]);
        mma4(acc[2 * i + 1], T1, R[i][2], R[i][3]);
        if (i >= 4) {
            mma4(acc[2 * i], N0, R[i - 4][0], R[i - 4][1]);
            mma4(acc[2 * i + 1], N1, R[i - 4][2], R[i - 4][3]);
        }
    }
    const uint32_t b = v8 + PLANE + 112;
    const uint32_t bz = (m & 1) ? priv : b, bm = (m & 1) ? b : b + 512;
    const uint32_t M[4] = {lds32(pb + 4 * 520), lds32(pb + 4 * 528), lds32v(pp + 32), lds32(pp + 64)};
#pragma unroll
    for (int i = 0; i < 6; i++) {
        uint32_t V[4];
        ldsm4(V, i < 2 ? bz + ((m & 1) ? 0 : i * 256) : bm + (i - 2) * 256);
        mma4(acc[2 * i + 4], M, V[0], V[1]);
        mma4(acc[2 * i + 5], M, V[2], V[3]);
    }
}

__device__ __forceinline__ uint32_t ones2(int c, int lo, int n) {
    return (((uint32_t)(c - lo) < (uint32_t)n) ? 0x3f80u : 0u) | (((uint32_t)(c + 1 - lo) < (uint32_t)n) ? 0x3f800000u : 0u);
}
template <int L1, int N1, int L2, int N2, int D>
__device__ __forceinline__ void box_ones(uint32_t dst, int d) { sts128(dst, ones2(d, L1, N1), ones2(d, L2, N2), ones2(d + D, L1, N1), ones2(d + D, L2, N2)); }
__device__ __forceinline__ uint32_t tok_at(int T) { return PLANE * ((T >> 3) & 1) + 16 * ((T >> 4) + 8) + 2 * (T & 7); }
__device__ __forceinline__ float left_col(float cur, float prev, int lane) {
    return __shfl_sync(0xffffffffu, (lane & 3) == 3 ? prev : cur, lane + 3, 4);
}
struct Tails {
    uint4 q4, q8, B4[5], ad;
    uint2 B8[8];
    uint32_t W[2][4], A[2][2][4];
    float p1, p3, p8;
    static __host__ __device__ constexpr bool is8(int k) { return k >= 4 && (TORD ? (k & 1) : (k & 4) == 0); }
    static __host__ __device__ constexpr int grp(int k) { return k < 4 ? k : TORD ? (k - 4) / 2 + (is8(k) ? 0 : 4) : (k & 3) + 4 * ((k - 4) >> 3) + (is8(k) ? 0 : 4); }
    __device__ __forceinline__ void load(int k, uint32_t priv) {
        uint32_t* w = W[k & 1];
        const uint32_t o = priv + 128 * grp(k);
        if (is8(k)) {
            const uint2 vy = lds64(o + ad.w), vx = lds64(o + ad.z);
            w[0] = vy.x; w[1] = vy.y; w[2] = vx.x; w[3] = vx.y;
        } else { w[0] = lds32(o + ad.y); w[1] = lds32(o + ad.x + 16); w[2] = lds32(o + ad.x); w[3] = lds32v(o + ad.y); }
    }
    __device__ __forceinline__ void box(int k, int lane) {
        const uint32_t* w = W[k & 1];
        const uint4 q = is8(k) ? q8 : q4;
        uint32_t (&a)[2][4] = A[k & 1];
        float X[4], Y[4];
        mma_bf16_z(Y, q.x, q.y, q.z, q.w, w[0], w[1]);
        mma_bf16_z(X, q.x, q.y, q.z, q.w, w[2], w[3]);
        a[0][0] = pack_bf16(X[0], X[1]); a[0][1] = pack_bf16(Y[0], Y[1]);
        if (is8(k)) {
            a[0][2] = pack_bf16(left_col(Y[3], p8, lane), Y[2]); a[0][3] = pack_bf16(X[2], X[3]);
            p8 = Y[3];
        } else {
            a[0][2] = pack_bf16(X[2], X[3]); a[0][3] = pack_bf16(Y[2], Y[3]);
            a[1][0] = pack_bf16(left_col(Y[1], p1, lane), Y[0]); a[1][1] = pack_bf16v(X[0], X[1]);
            a[1][2] = pack_bf16(left_col(Y[3], p3, lane), Y[2]); a[1][3] = pack_bf16v(X[2], X[3]);
            p1 = Y[1]; p3 = Y[3];
        }
    }
    __device__ __forceinline__ void taps(int k, float (&acc)[16][4]) {
        const int G = grp(k);
        if (is8(k)) {
#pragma unroll
            for (int b = 0; b < 8; b++) if (G + 8 + b < 16) mma4(acc[G + 8 + b], A[k & 1][0], B8[b].x, B8[b].y);
        } else {
#pragma unroll
            for (int b = 0; b < 5; b++) if (G + 4 + b < 16) mma4(acc[G + 4 + b], A[k & 1][0], B4[b].x, B4[b].y);
#pragma unroll
            for (int b = 0; b < 5; b++) if (G + 4 + b < 16) mma4(acc[G + 4 + b], A[k & 1][1], B4[b].z, B4[b].w);
        }
    }
    __device__ __forceinline__ void start(uint32_t lc, uint32_t priv, uint32_t tap, int lane) {
        ad = lds128(lc + 1024); q4 = lds128(lc); q8 = lds128(lc + 512);
        p1 = p3 = p8 = 0.f;
        load(0, priv); load(1, priv);
#pragma unroll
        for (int i = 0; i < 5; i++) B4[i] = lds128(priv + T_S4 + 128 * i + 2 * tap);
        box(0, lane);
    }
    template <int K0, int K1>
    __device__ __forceinline__ void run(float (&acc)[16][4], uint32_t priv, uint32_t tap, int lane) {
#pragma unroll
        for (int k = K0; k < K1; k++) {
            if (k + 2 < 20) load(k + 2, priv);
            if (k == 4) {
#pragma unroll
                for (int i = 0; i < 8; i++) B8[i] = lds64(priv + T_S8 + 64 * i + tap);
            }
            if (k + 1 < 20) box(k + 1, lane);
            taps(k, acc);
        }
    }
};
__device__ __forceinline__ void lane_consts(uint32_t dst, int unit, int lane) {
    const int g = lane >> 2, t = lane & 3, m = lane >> 3, r = lane & 7;
    if (unit == 0) box_ones<0, 5, 5, 3, 8>(dst, 2 * t - g);
    else if (unit == 1) box_ones<1, 7, 0, 9, 2>(dst, 4 * t - g);
    else if (unit == 2) sts128(dst, tok_at(16 * g - 10 + 2 * t), tok_at(16 * g - 2 + 2 * t), tok_at(16 * g - 12 + 4 * t), tok_at(16 * g - 4 + 4 * t));
    else {
        const uint32_t low = 64 * (t >> 1) + 32 * (g & 1) + 16 * (t & 1), hi = (lane & 24) + (lane & 16);
        sts128(dst, 128 * hi + low, 512 * (4 * (r & 2) + 2 * m + (r & 1)) + 16 * ((r >> 2) ^ (2 * (r & 3))), 32 * hi + low, 8 * (6 + g - 2 * t));
    }
}

__device__ __forceinline__ uint32_t mean_std(float mu, float var) { return pack_bf16(mu, sqrtaf(bf_round(bf_round(var) + 1e-5f))); }
__device__ __noinline__ uint2 ln_centred(uint32_t sb, float mu) {
    const int lane = threadIdx.x & 31;
    uint32_t ms = 0;
    float res = 0.f, ri = 0.f;
#pragma unroll 1
    for (int mode = 0; mode < 2; mode++) {
#pragma unroll 1
        for (int rr = 0; rr < 16; rr++) {
            const float c0 = __shfl_sync(0xffffffffu, mu, rr), rj = __shfl_sync(0xffffffffu, ri, rr);
            float c = 0.f;
#pragma unroll 1
            for (int k = 0; k < 16; k++) {
                const uint32_t q = lds32(sb + OFF_ROWS + k * 2048 + rr * 128 + ((lane * 4) ^ ((rr & 7) << 4))), wq = lds32(sb + OFF_GP + k * 128 + lane * 4);
                const float d0 = bf_lo(q) - c0, d1 = bf_hi(q) - c0;
                if (mode) c = fmaf(bf_round(bf_round(d0) * rj), bf_lo(wq), fmaf(bf_round(bf_round(d1) * rj), bf_hi(wq), c));
                else c = fmaf(d0, d0, fmaf(d1, d1, c));
            }
#pragma unroll 1
            for (int o = 16; o; o >>= 1) c += __shfl_xor_sync(0xffffffffu, c, o);
            if ((lane & 15) == rr) res = c;
        }
        if (mode == 0) { ms = mean_std(mu, res * (1.f / DM)); mu = bf_lo(ms); ri = rcpf(bf_hi(ms)); }
    }
    named_sync(1, 128);
    return make_uint2(ms, __float_as_uint(res));
}

__device__ __forceinline__ void router_cta(uint32_t* scr, uint32_t sb, uint32_t zero, int tid, int warp) {
    const int lane = tid & 31;
    const uint32_t cand = sb + 128;
    const uint32_t epoch = ld_relaxed_32(scr + S_EPOCH);
    if (tid < 128) st_relaxed_32(scr + S_SEL + tid, 0u);
    if (tid == 0) sts32(sb + 64, cand);
    sts128(cand + 16 * tid, 0, 0, 0, 0);
    asm volatile("fence.acq_rel.gpu;" ::: "memory");
    const uint32_t tag = (epoch + 1u) | 0x8000u;
    STAMP(0); GSTAMP(1);
    uint32_t* const psel = scr + S_SEL + 32 * (lane & 3);
    const uint32_t cnt = sb + 64 + (tid & zero);
    uint32_t it = 0;
    uint4 q;
#pragma unroll 1
    do {
        q = ld_relaxed_128(scr + S_KEY + 4 * tid);
        if (++it > SPIN_LIMIT) __trap();
    } while (!__all_sync(0xffffffffu, (((q.x ^ tag) | (q.y ^ tag) | (q.z ^ tag) | (q.w ^ tag)) & 0xffffu) == 0));
    STAMP(2);
    uint32_t key[4] = {q.x, q.y, q.z, q.w};
#pragma unroll
    for (int j = 0; j < 4; j++) key[j] = ((key[j] ^ ((uint32_t)((int)key[j] >> 31) | 0x80000000u)) & 0xffff0000u) | (0xffffu - (uint32_t)(4 * tid + j));
    const uint32_t gm = __reduce_max_sync(0xffffffffu, max(max(key[0], key[1]), max(key[2], key[3])));
    sts32(sb + 4 * warp, gm);
    __syncthreads();
    const uint2 pr = lds64(sb + 8 * (lane & 7));
    const uint32_t tau = __reduce_min_sync(0xffffffffu, max(pr.x, pr.y));
    asm volatile("{\n\t.reg .pred p<4>;\n\t.reg .u32 a<4>;\n\t"
                 "setp.ge.u32 p0, %0, %4;\n\tsetp.ge.u32 p1, %1, %4;\n\tsetp.ge.u32 p2, %2, %4;\n\tsetp.ge.u32 p3, %3, %4;\n\t"
                 "@p0 atom.shared.add.u32 a0, [%5], 4;\n\t@p1 atom.shared.add.u32 a1, [%5], 4;\n\t"
                 "@p2 atom.shared.add.u32 a2, [%5], 4;\n\t@p3 atom.shared.add.u32 a3, [%5], 4;\n\t"
                 "@p0 st.shared.u32 [a0], %0;\n\t@p1 st.shared.u32 [a1], %1;\n\t@p2 st.shared.u32 [a2], %2;\n\t@p3 st.shared.u32 [a3], %3;\n\t}"
                 ::"r"(key[0]), "r"(key[1]), "r"(key[2]), "r"(key[3]), "r"(tau), "r"(cnt) : "memory");
    __syncthreads();
    STAMP(6);
    const uint32_t c0 = lds32v(cand + 4 * lane);
    uint2 k = lds64(cand + 8 * warp);
    const uint32_t end = __shfl_sync(0xffffffffu, lds32v(sb + 64), 0);
    uint32_t i = cand + 8 * warp;
#pragma unroll 1
    do {
        uint32_t r0 = __popc(__ballot_sync(0xffffffffu, c0 > k.x)), r1 = __popc(__ballot_sync(0xffffffffu, c0 > k.y));
#pragma unroll 1
        for (uint32_t j = cand + 128; j < end; j += 128) {
            const uint32_t c = lds32(j + 4 * lane);
            r0 += __popc(__ballot_sync(0xffffffffu, c > k.x)); r1 += __popc(__ballot_sync(0xffffffffu, c > k.y));
        }
        const uint32_t rk = (lane & 4) ? r1 : r0;
        if (rk < 8 && lane < 8) st_relaxed_64(psel + 2 * rk, (lane & 4) ? k.y : k.x, tag);
        i += 128;
        k = lds64(i);
    } while (i < end);
    STAMP(4); GSTAMP(5);
    if (tid == 0) st_relaxed_32(scr + S_EPOCH, epoch + 1u);
}

__global__ void __cluster_dims__(2, 1, 1) __launch_bounds__(NTHR, 1)
fused_kernel(const __grid_constant__ Ptrs p, const __grid_constant__ Maps maps) {
    extern __shared__ __align__(1024) unsigned char smem[];
    const uint32_t sb = s_u32(smem);
    const int tid = threadIdx.x, lane = tid & 31;
    const int warp = __shfl_sync(0xffffffffu, tid >> 5, 0);
    const int b = blockIdx.x, h = b & 1, cl = b >> 1;
    const uint32_t bar0 = sb + OFF_BAR;
    const int m = lane >> 3, r = lane & 7;
    if (b >= NCTA) {
        if (b == NCTA) router_cta(p.scr, sb, p.zero, tid, warp);
        return;
    }
    if (warp < 8) {
        const int w = warp, dch = 8 * b + w;
        STAMP(0);
        if (INC_AT == 0) asm volatile("setmaxnreg.inc.sync.aligned.u32 %0;" ::"n"(NREG));
        const int po = dch * NMODE + 4 * lane;
        const uint2 la = ldg64(p.logA + po), aim = ldg64(p.Aim + po), cre = ldg64(p.Cre + po), cim = ldg64(p.Cim + po);
        const uint32_t ldt16 = ldg16(p.ldt + dch), dsk16 = ldg16(p.dsk + dch);
        cluster_arrive();
        if (CW_EARLY) cluster_wait();
        if (INC_AT == 1) asm volatile("setmaxnreg.inc.sync.aligned.u32 %0;" ::"n"(NREG));
        const uint32_t priv = sb + OFF_PRIV + w * PRIV;
        const int g = lane >> 2, t = lane & 3;
        const uint32_t* sp = p.scr + S_STAT + 2048 * (cl & 3) + 256 * w + 16 * t + 2 * g;
        uint2 sq[4];
        float kacc[5][4], kscale;
        {
            const uint32_t m2 = as_u(__hmax2(__hmax2(__habs2(as_b2(cre.x)), __habs2(as_b2(cre.y))), __hmax2(__habs2(as_b2(cim.x)), __habs2(as_b2(cim.y)))));
            const uint32_t eb = min(max(__reduce_max_sync(0xffffffffu, max(m2 << 16, m2)) >> 23, 1u), 252u);
            const float dt = bf_round(ex2f(bf_lo(ldt16) * L2E));
            float s0[4];
            mma_bf16_z(s0, ONES, ONES, ONES, ONES, cre.x, cre.y);
            STAMP(1);
            kgen_mma(kacc, priv, lane, la, aim, cre, cim, dt, (253u - eb) * 0x00800080u);
            STAMP(2);
            if (INC_AT == 2) asm volatile("setmaxnreg.inc.sync.aligned.u32 %0;" ::"n"(NREG));
            if (!CW_EARLY) cluster_wait();
            __syncwarp();
            if (elect_one()) mbar_arrive(bar0 + 8 * B_KG);
#pragma unroll
            for (int i = 0; i < 4; i++) sq[i] = ld_relaxed_64(sp + 64 * i);
            float k0 = s0[0] + s0[1];
            k0 += __shfl_xor_sync(0xffffffffu, k0, 1);
            k0 += __shfl_xor_sync(0xffffffffu, k0, 2);
            kscale = (dt + dt) * __uint_as_float((eb + 1u) << 23);
            kgen_tables(kacc, priv, lane, kscale, fmaf(k0, dt + dt, bf_lo(dsk16) + 1.f));
        }
        STAMP(3);
        {
            mbar_wait(bar0 + 8 * B_TAG, 0);
            const uint32_t want = lds32(sb + OFF_MISC);
            uint32_t s2[4];
#pragma unroll 1
            while (true) {
#pragma unroll
                for (int i = 0; i < 4; i++) s2[i] = __byte_perm(sq[i].x, sq[i].y, 0x7632) ^ want;
                if (__all_sync(0xffffffffu, ((s2[0] | s2[1] | s2[2] | s2[3]) & 0x80008000u) == 0)) break;
#pragma unroll
                for (int i = 0; i < 4; i++) sq[i] = ld_relaxed_64(sp + 64 * i);
            }
            STAMP(4);
            mbar_wait(bar0 + 8 * (B_X + w), 0);
            STAMP(5);
            uint32_t v[8][4];
#pragma unroll
            for (int i = 0; i < 4; i++) {
                const uint2 rc = recip2(s2[i]);
#pragma unroll
                for (int hf = 0; hf < 2; hf++) {
                    const __nv_bfloat162 mm = __low2bfloat162(as_b2(hf ? sq[i].y : sq[i].x));
                    const __nv_bfloat162 rh = hf ? __high2bfloat162(as_b2(rc.x)) : __low2bfloat162(as_b2(rc.x));
                    const __nv_bfloat162 rl = hf ? __high2bfloat162(as_b2(rc.y)) : __low2bfloat162(as_b2(rc.y));
                    const uint4 q = lds128(sb + OFF_X + 8192 * w + 32 * lane + ((h ^ (g & 1)) << 4) + 2048 * i + 1024 * hf);
                    uint32_t* o = v[2 * i + hf];
                    o[0] = normalize2(q.x, mm, rh, rl); o[1] = normalize2(q.y, mm, rh, rl); o[2] = normalize2(q.z, mm, rh, rl); o[3] = normalize2(q.w, mm, rh, rl);
                }
            }
            mbar_wait(bar0 + 8 * B_KG, 0);
            const uint32_t dst = sb + OFF_PRIV + (2 * m + (r & 1)) * PRIV + 128 + 256 * w + 16 * (r >> 1);
#pragma unroll
            for (int i = 0; i < 8; i++) stsm4t(dst + 64 * (i >> 1) + PLANE * (i & 1), v[i]);
            __syncwarp();
            if (elect_one()) { mbar_arrive(bar0 + 8 * B_VT); mbar_arrive_peer(mapa(bar0 + 8 * B_PV, h ^ 1)); }
        }
        if (INC_AT == 3) { __syncwarp(); asm volatile("setmaxnreg.inc.sync.aligned.u32 %0;" ::"n"(NREG)); }
        kgen_tables2(kacc, priv, lane, kscale);
        if (INC_AT == 4) asm volatile("setmaxnreg.inc.sync.aligned.u32 %0;" ::"n"(NREG));
        float acc[16][4];
        dense_phase(acc, priv, lane, [&]() {
            mbar_wait(bar0 + 8 * B_VT, 0);
            STAMP(6);
        }, [&]() { mbar_wait(bar0 + 8 * B_PV, 0); });
        STAMP(7);
        const uint32_t sd = sb + OFF_X + 512 * (8 * h + w) + 16 * (lane ^ (2 * (w & 1) + 4 * h));
        const uint32_t sd0 = mapa(sd + 8192, 0), sd1 = mapa(sd, 1);
        auto send = [&](auto PT) {
            constexpr int pt = decltype(PT)::value;
#pragma unroll
            for (int i = 0; i < 2; i++) {
                const float* c0 = acc[4 * pt + 2 * i];
                const float* c1 = acc[4 * pt + 2 * i + 1];
                asm volatile("st.async.weak.shared::cluster.mbarrier::complete_tx::bytes.v4.b32 [%0 + %6], {%1,%2,%3,%4}, [%5];"
                             ::"r"(i ? sd1 : sd0), "r"(pack_bf16(c0[0], c0[1])), "r"(pack_bf16(c0[2], c0[3])), "r"(pack_bf16(c1[0], c1[1])),
                               "r"(pack_bf16(c1[2], c1[3])), "r"(mapa(bar0 + 8 * (B_RECV + pt), i)), "n"(16384 * pt) : "memory");
            }
        };
        const uint4 lc = lds128(sb + OFF_LC + 1536 + 16 * lane);
        const uint32_t stg = (priv + T_DENSE + 63) & ~127u, so = stg + lc.z;
        const uint32_t xa = sb + OFF_X + 16384 * (w >> 2) + 8192 * h + 256 * (w & 3) + lc.x;
        const uint32_t sa = sb + OFF_X + 16384 * (w >> 2) + 8192 * (h ^ 1) + 128 * (w & 3) + lc.y;
        constexpr int ST2 = -2048;
        auto finish = [&](int ph) {
            if (ph == FINE) STAMP(1);
            const int box = 4 * ph + 2 * (w >> 2) + h;
            uint4 x[4];
            uint32_t s[4][4];
#pragma unroll
            for (int i = 0; i < 4; i++) x[i] = lds128((xa ^ (8 * (i & 2))) + 32768 * ph + 2048 * (i & 1) + 64 * (i & 2));
            if (ph == FINE) STAMP(2);
            mbar_wait(bar0 + 8 * (B_RECV + 2 * ph + (w >> 2)), 0);
            if (ph == FINE) STAMP(3);
            const uint32_t routed = __shfl_sync(0xffffffffu, lds32(sb + OFF_MISC + 4), 0);
#pragma unroll
            for (int i = 0; i < 4; i++) ldsm4t(s[i], (sa ^ (32 * i)) + 32768 * ph);
#pragma unroll
            for (int i = 0; i < 4; i++) { s[i][0] = badd2(x[i].x, s[i][0]); s[i][1] = badd2(x[i].y, s[i][1]); s[i][2] = badd2(x[i].z, s[i][2]); s[i][3] = badd2(x[i].w, s[i][3]); }
            if (ph == FINE) STAMP(4);
            if ((routed >> (4 * box + (w & 3))) & 1) {
                const uint32_t tk = 256 * box + 128 * (g >> 2) + 32 * (t >> 1) + 16 * (g & 1) + 4 * (g & 2) + 2 * (w & 3);
                const uint32_t mk[2] = {lds32(sb + OFF_MISC + 32 + 4 * (tk >> 5)) >> (tk & 31), lds32(sb + OFF_MISC + 40 + 4 * (tk >> 5)) >> (tk & 31)};
                __nv_bfloat16* o = p.out + (size_t)tk * DM + 16 * cl + 8 * (t & 1);
#pragma unroll
                for (int i = 0; i < 4; i++)
                    asm volatile("{\n\t.reg .pred p;\n\tsetp.eq.u32 p, %6, 0;\n\t@!p st.shared.v4.u32 [%1], {%2,%3,%4,%5};\n\t@p st.global.v4.u32 [%0], {%2,%3,%4,%5};\n\t}"
                                 ::"l"(o + (64 * (i & 1) + (i >> 1)) * DM), "r"((xa ^ (8 * (i & 2))) + 32768 * ph + 2048 * (i & 1) + 64 * (i & 2)),
                                   "r"(s[i][0]), "r"(s[i][1]), "r"(s[i][2]), "r"(s[i][3]), "r"(mk[i & 1] & (1u << (i >> 1))) : "memory");
            } else {
#pragma unroll
                for (int i = 0; i < 4; i++) sts128(so + ST2 * ph + 512 * (i & 1) + 64 * (i & 2), s[i][0], s[i][1], s[i][2], s[i][3]);
                fence_async();
                if (ph == FINE) STAMP(5);
                __syncwarp();
                if (elect_one()) {
                    asm volatile("cp.async.bulk.tensor.5d.global.shared::cta.bulk_group [%0, {%2, %5, %3, %5, %4}], [%1];"
                                 ::"l"(&maps.out), "r"(stg + ST2 * ph), "r"(16 * cl), "r"(2 * (w & 3)), "r"(4 * box), "r"(0) : "memory");
                }
            }
        };
        Tails tl;
        tl.start(sb + OFF_LC + 16 * lane, priv, lc.w, lane);
        send(IC<0>());
        tl.run<0, 4>(acc, priv, lc.w, lane);
        send(IC<1>());
        STAMP(8);
        tl.run<4, FIN_A>(acc, priv, lc.w, lane);
        if (FIN_A == FIN_B || w < 4) finish(0);
        tl.run<FIN_A, FIN_B>(acc, priv, lc.w, lane);
        if (FIN_A != FIN_B && FIN_B < 12 && w >= 4) finish(0);
        tl.run<FIN_B, 12>(acc, priv, lc.w, lane);
        send(IC<2>());
        STAMP(9);
        if (FIN_A != FIN_B && FIN_B == 12 && w >= 4) finish(0);
        tl.run<12, 20>(acc, priv, lc.w, lane);
        STAMP(11);
        send(IC<3>());
        finish(1);
        STAMP(12);
        __syncwarp();
        if (elect_one()) mbar_arrive(bar0 + 8 * B_ST);
        cluster_arrive();
        asm volatile("cp.async.bulk.commit_group;" ::: "memory");
        asm volatile("cp.async.bulk.wait_group.read 0;" ::: "memory");
        STAMP(13); GSTAMP(15);
    } else if (warp < 12) {
        const int a = warp - 8, at = 32 * a + lane, g = lane >> 2, t = lane & 3;
        STAMP(0);
        if (elect_one()) {
            const uint32_t cnt = a == 3 ? 0x48411122u : a == 2 ? 0x44444444u : 0x11111111u, tx = a == 0 ? 0x44444444u : a == 3 ? 0x00084444u : 0u;
#pragma unroll 1
            for (int i = 0; i < 8; i++) {
                mbar_init(bar0 + 64 * a + 8 * i, (cnt >> (4 * i)) & 15);
                const uint32_t n = (tx >> (4 * i)) & 15;
                if (n) mbar_expect_tx(bar0 + 64 * a + 8 * i, n << 11);
            }
            if (a < 3) mbar_init(bar0 + 8 * (B_KG + a), 8);
            asm volatile("fence.mbarrier_init.release.cluster;" ::: "memory");
            fence_async();
        }
        __syncwarp();
        cluster_arrive();
        const uint32_t epoch = ld_relaxed_32(p.scr + S_EPOCH);
        uint32_t* const pst = p.scr + S_STAT + 2048 * a + 16 * b + 2 * r + m;
        uint32_t* const pky = p.scr + S_KEY + 16 * b + at;
        if (lane < 16) st_relaxed_32(pst, 0u);
        if (at < 16) st_relaxed_32(pky, 0u);
        uint32_t* const py = p.scr + S_Y + 1024 * ((cl & ~3) + a) + 128 * (b & 7) + 32 * t + 4 * g;
        st_relaxed_128(py, 0u, 0u, 0u, 0u);
        const uint32_t gp = sb + OFF_GP;
        sts32(gp + 2048 + 4 * lane, ONES);
        lane_consts(sb + OFF_LC + 16 * at, a, lane);
        cluster_wait();
        STAMP(1);
        mbar_wait(bar0 + 8 * B_WR, 0);
        float ws[4] = {0.f, 0.f, 0.f, 0.f};
#pragma unroll 1
        for (int k = 0; k < 4; k++) {
            const uint4 q = lds128(gp + k * 512 + lane * 16);
            mma_bf16(ws, ONES, ONES, ONES, ONES, q.x, q.y);
            mma_bf16(ws, ONES, ONES, ONES, ONES, q.z, q.w);
        }
        float wsum = ws[0] + ws[1];
        wsum += __shfl_xor_sync(0xffffffffu, wsum, 1);
        wsum += __shfl_xor_sync(0xffffffffu, wsum, 2);
        const uint32_t hsel = (epoch & 1) * (GU_CTAS * 128), want = (epoch & 1) ? 0x00008000u : 0x80000000u;
        const uint32_t tbit = (epoch ^ m) << 31, ktag = ((epoch + 1u) | 0x8000u) & 0xffffu;
        if (a == 0) { sts64(sb + OFF_MISC + 32 + 8 * lane, 0u, 0u); sts32(sb + OFF_MISC, want); }
        __syncwarp();
        if (elect_one()) mbar_arrive(bar0 + 8 * B_TAG);
        if (b < GU_CTAS) st_relaxed_32(p.scr + S_H + (GU_CTAS * 128 - hsel) + b * 128 + at, 0u);
        {
            uint32_t ra[4], rb[4];
#pragma unroll
            for (int i = 0; i < 4; i++) {
                ra[i] = sb + OFF_ROWS + 2048 * a + 128 * (r + 8 * (m & 1)) + (((2 * i + (m >> 1)) ^ r) << 4);
                rb[i] = sb + OFF_ROWS + 2048 * a + 128 * (r + 8 * (m >> 1)) + (((2 * i + (m & 1)) ^ r) << 4);
            }
            uint32_t wa = r == 1 ? gp + 128 * a + 16 * m : gp + 2048;
            const uint32_t wstep = r == 1 ? 512 : 0;
            float cs[2][4] = {}, q1[2][4] = {}, q2[2][4] = {};
#pragma unroll 1
            for (int k = 0; k < 4; k++) {
                uint32_t x[4][4], z[4][4], wf[2][4];
                ldsm4(wf[0], wa); ldsm4(wf[1], wa + 64);
                mbar_wait(bar0 + 8 * (B_ROW + k), 0);
                STAMP(2);
#pragma unroll
                for (int i = 0; i < 4; i++) {
                    ldsm4(x[i], ra[i] + 8192 * k);
                    if (LN_DUP) ldsm4(z[i], rb[i] + 8192 * k);
                    else { z[i][0] = x[i][0]; z[i][1] = x[i][2]; z[i][2] = x[i][1]; z[i][3] = x[i][3]; }
                }
#pragma unroll
                for (int i = 0; i < 4; i++) {
                    mma_bf16(cs[i & 1], x[i][0], x[i][1], x[i][2], x[i][3], wf[i >> 1][2 * (i & 1)], wf[i >> 1][2 * (i & 1) + 1]);
                    mma_bf16(q1[i & 1], x[i][0], x[i][1], x[i][2], x[i][3], z[i][0], z[i][1]);
                    mma_bf16(q2[i & 1], x[i][0], x[i][1], x[i][2], x[i][3], z[i][2], z[i][3]);
                }
                wa += wstep;
            }
            const uint32_t pa = gp + 2304 + 256 * a;
#pragma unroll
            for (int i = 0; i < 4; i++) cs[0][i] += cs[1][i];
            if (t == 0) sts128f(pa + 16 * g, cs[0]);
            if (t == (g >> 1)) sts64(pa + 128 + 8 * g, __float_as_uint((g & 1) ? q1[0][1] + q1[1][1] : q1[0][0] + q1[1][0]),
                                     __float_as_uint((g & 1) ? q2[0][3] + q2[1][3] : q2[0][2] + q2[1][2]));
            named_sync(1, 128);
            uint2 u[4];
            float sq4[4];
#pragma unroll
            for (int i = 0; i < 4; i++) {
                u[i] = lds64(gp + 2304 + 256 * i + 16 * r + 8 * (m & 1));
                sq4[i] = lds32f(gp + 2304 + 128 + 256 * i + 8 * r + 4 * (m & 1));
            }
            const float mu = ((__uint_as_float(u[0].x) + __uint_as_float(u[1].x)) + (__uint_as_float(u[2].x) + __uint_as_float(u[3].x))) * (1.f / DM);
            const float sw = (__uint_as_float(u[0].y) + __uint_as_float(u[1].y)) + (__uint_as_float(u[2].y) + __uint_as_float(u[3].y));
            const float e2 = ((sq4[0] + sq4[1]) + (sq4[2] + sq4[3])) * (1.f / DM), var = fmaf(-mu, mu, e2);
            uint32_t ms = mean_std(mu, var);
            float sc = (sw - bf_round(mu) * wsum) * rcpf(bf_hi(ms));
            if (__any_sync(0xffffffffu, !(e2 <= 5.f * var))) {
                const uint2 c = ln_centred(sb, mu);
                ms = c.x; sc = __uint_as_float(c.y);
            }
            if (lane < 16) st_relaxed_32(pst, ms | tbit);
            if (at < 16) st_relaxed_32(pky, pack_bf16(0.f, sc) | ktag);
            if (lane < 8) mbar_arrive(bar0 + 8 * (B_EMPTY + lane));
        }
        __syncwarp();
        cluster_arrive();
        STAMP(3); GSTAMP(14);
        uint32_t mykey;
        {
            const uint32_t* sl = p.scr + S_SEL + 32 * (cl & 3) + 2 * g;
            uint2 q;
#pragma unroll 1
            do {
                __nanosleep(SEL_SLEEP);
                q = ld_relaxed_64(sl);
            } while (!__all_sync(0xffffffffu, q.y == ((epoch + 1u) | 0x8000u)));
            mykey = q.x;
        }
        STAMP(4);
        if (a == 0) {
            const uint32_t tok = ~mykey & 0xffffu;
            if (t == 0) asm volatile("red.shared.or.b32 [%0], %1;" ::"r"(sb + OFF_MISC + 32 + 4 * (tok >> 5)), "r"(1u << (tok & 31u)) : "memory");
            sts32(sb + OFF_MISC + 4, __reduce_or_sync(0xffffffffu, 1u << (4 * (tok >> 8) + ((tok >> 1) & 3))));
            __syncwarp();
            if (elect_one()) { mbar_arrive(bar0 + 8 * B_RECV); mbar_arrive(bar0 + 8 * (B_RECV + 1)); }
        }
        if (b < GU_CTAS) {
            const uint32_t tok = 0xffffu - (mykey & 0xffffu);
            {
                const uint32_t tk = __shfl_sync(0xffffffffu, tok, 16 * h + 4 * a);
                if (elect_one())
                    asm volatile("cp.async.bulk.shared::cluster.global.mbarrier::complete_tx::bytes.multicast::cluster [%0], [%1], 2048, [%2], %3;"
                                 ::"r"(sb + OFF_XS + (4 * h + a) * ROW_PITCH), "l"(p.u + (size_t)tk * DM), "r"(bar0 + 8 * B_XS), "h"((uint16_t)3) : "memory");
            }
            uint2 rec;
#pragma unroll 1
            do {
                rec = ld_relaxed_64(p.scr + S_STAT + 2048 * a + (tok & ~15u) + 2 * (tok & 7u));
            } while (!__all_sync(0xffffffffu, ((__byte_perm(rec.x, rec.y, 0x7632) ^ want) & 0x80008000u) == 0));
            const uint32_t mst = (tok & 8u) ? rec.y : rec.x;
            const uint32_t m2 = __byte_perm(mst, 0, 0x1010);
            const float rs = rcpf(__uint_as_float(mst & 0x7fff0000u));
            const float r0 = __shfl_sync(0xffffffffu, rs, 8 * t), r1 = __shfl_sync(0xffffffffu, rs, 8 * t + 4);
            float gacc[4][4];
#pragma unroll
            for (int i = 0; i < 4; i++) { gacc[i][0] = gacc[i][1] = gacc[i][2] = gacc[i][3] = 0.f; }
            const int k = r + 8 * (m >> 1);
            uint32_t wa[4];
#pragma unroll
            for (int mt = 0; mt < 4; mt++) wa[mt] = 1024 * a + (((m & 1) * 4096) ^ p.up_first) + k * 64 + ((((k >> 1) & 3) ^ mt) << 4);
            const uint32_t xa = sb + OFF_XS + r * ROW_PITCH + 32 * a + 16 * (m & 1) + 128 * (m >> 1);
#pragma unroll 1
            for (int c = 0; c < 4; c++) {
                uint32_t af[4][4][4], xb[2][4];
                const uint32_t half = sb + OFF_RING + 32768 * (c & 1), fb = bar0 + 8 * B_FULL + 32 * (c & 1);
#pragma unroll
                for (int j = 0; j < 4; j++) {
                    mbar_wait(fb + 8 * j, c >> 1);
                    if (j == 3) STAMP(12);
#pragma unroll
                    for (int mt = 0; mt < 4; mt++) ldsm4t(af[j][mt], wa[mt] + half + j * 8192);
                    __syncwarp();
                    if (elect_one()) mbar_arrive(fb + 8 * (B_EMPTY - B_FULL + j));
                    if (j == GU_SPLIT) {
                        mbar_wait(bar0 + 8 * B_XS, 0);
#pragma unroll
                        for (int i = 0; i < 2; i++) {
                            ldsm4(xb[i], xa + 512 * c + 256 * i);
#pragma unroll
                            for (int e = 0; e < 4; e++) xb[i][e] = as_u(__hsub2(as_b2(xb[i][e]), as_b2(m2)));
                        }
                    }
                    if (j == 3) STAMP(1);
                    if (j >= GU_SPLIT) {
#pragma unroll
                        for (int ks = j == GU_SPLIT ? 0 : j; ks <= j; ks++) {
#pragma unroll
                            for (int mt = 0; mt < 4; mt++)
                                mma_bf16v(gacc[mt], af[ks][mt], xb[ks >> 1][2 * (ks & 1)], xb[ks >> 1][2 * (ks & 1) + 1]);
                        }
                    }
                }
            }
            STAMP(6);
#pragma unroll
            for (int mt = 0; mt < 4; mt++) sts128f(gp + 2048 * a + mt * 512 + lane * 16, gacc[mt]);
            named_sync(1, 128);
            {
                uint4 q[4];
#pragma unroll
                for (int wq = 0; wq < 4; wq++) q[wq] = lds128(gp + 2048 * wq + 16 * at);
                const uint32_t g2 = pack_bf16(r0 * ((__uint_as_float(q[0].x) + __uint_as_float(q[1].x)) + (__uint_as_float(q[2].x) + __uint_as_float(q[3].x))),
                                              r1 * ((__uint_as_float(q[0].y) + __uint_as_float(q[1].y)) + (__uint_as_float(q[2].y) + __uint_as_float(q[3].y))));
                const uint32_t u2 = pack_bf16(r0 * ((__uint_as_float(q[0].z) + __uint_as_float(q[1].z)) + (__uint_as_float(q[2].z) + __uint_as_float(q[3].z))),
                                              r1 * ((__uint_as_float(q[0].w) + __uint_as_float(q[1].w)) + (__uint_as_float(q[2].w) + __uint_as_float(q[3].w))));
                const uint32_t s2 = pack_bf16(bf_lo(g2) * rcpf(1.f + ex2f(-L2E * bf_lo(g2))), bf_hi(g2) * rcpf(1.f + ex2f(-L2E * bf_hi(g2))));
                uint32_t hw;
                asm volatile("movmatrix.sync.aligned.m8n8.trans.b16 %0, %1;" : "=r"(hw) : "r"(as_u(__hmul2(as_b2(s2), as_b2(u2)))));
                if (hw == 0u) hw = 0x80008000u;
                st_relaxed_32(p.scr + S_H + hsel + b * 128 + at, hw);
            }
            STAMP(7);
        }
        const uint32_t ytag = 1u + (epoch & 1);
        {
            const uint32_t* hp = p.scr + S_H + hsel + (b & 7) * 1792 + 4 * at;
            const uint32_t wa = sb + OFF_RING + 128 * (r + 8 * (m >> 1)) + (((2 * a + (m & 1)) ^ r) << 4);
            uint32_t af[4][4][4], hb[4];
            float dacc[4][4] = {};
            auto load_w = [&](int s) {
                mbar_wait(bar0 + 8 * (B_FULL + s), 0);
                if (s == 6) STAMP(13);
#pragma unroll
                for (int j = 0; j < 4; j++) ldsm4t(af[s & 3][j], wa + s * 8192 + j * 2048);
            };
            auto run = [&](int s) {
#pragma unroll
                for (int j = 0; j < 4; j++) {
                    if (!(j & 1)) ldsm4(hb, sb + OFF_XS + 16 * lane + 1024 * s + 256 * j);
                    mma_bf16v(dacc[j], af[s & 3][j], hb[2 * (j & 1)], hb[2 * (j & 1) + 1]);
                }
            };
#pragma unroll
            for (int s = 0; s < DN_PRE; s++) load_w(s);
            uint4 hq[4];
#pragma unroll 1
            do {
                __nanosleep(H_SLEEP);
#pragma unroll
                for (int j = 0; j < 4; j++) hq[j] = ld_relaxed_128(hp + (j < 3 ? 512 * j : 1280));
            } while (!__all_sync(0xffffffffu, min(min(hq[0].w, hq[1].w), min(hq[2].w, hq[3].w)) != 0));
#pragma unroll
            for (int j = 0; j < 4; j++) sts128(sb + OFF_XS + 16 * at + (j < 3 ? 2048 * j : 5120), hq[j].x, hq[j].y, hq[j].z, hq[j].w);
            STAMP(2);
#pragma unroll
            for (int s = DN_PRE; s < 4; s++) load_w(s);
            named_sync(1, 128);
            STAMP(8);
#pragma unroll
            for (int s = 0; s < 4; s++) run(s);
            load_w(4); load_w(5);
            if (DN_LAST) { run(4); run(5); load_w(6); }
            else { load_w(6); run(4); run(5); }
            run(6);
            uint32_t y[4];
#pragma unroll
            for (int j = 0; j < 4; j++) y[j] = (__float_as_uint((dacc[0][j] + dacc[1][j]) + (dacc[2][j] + dacc[3][j])) & ~3u) | ytag;
            st_relaxed_128(py, y[0], y[1], y[2], y[3]);
        }
        STAMP(9);
        {
            const uint32_t key = __shfl_sync(0xffffffffu, mykey, 8 * a + 4 * (m >> 1));
            const uint32_t tok = 0xffffu - (key & 0xffffu);
            const float sg = bf_round(rcpf(1.f + ex2f(-L2E * bf_lo(unorder_key(key >> 16)))));
            const uint32_t xo = sb + OFF_X + 32 * (tok & ~63u) + 128 * (tok & 15u) + 2 * (tok & 48u) + ((2 * (lane & 15)) ^ ((tok & 1u) << 4));
            if (((tok >> 8) & 1) == h) {
                const uint32_t* yp = p.scr + S_Y + 1024 * cl + 32 * a + 4 * r + 2 * (m & 1) + (m >> 1);
                uint32_t pp[8], bad;
#pragma unroll 1
                do {
                    bad = 0;
#pragma unroll
                    for (int q = 0; q < 8; q++) pp[q] = ld_relaxed_32(yp + 128 * q);
#pragma unroll
                    for (int q = 0; q < 8; q++) bad |= pp[q] ^ ytag;
                } while (bad & 3u);
                const float y = ((__uint_as_float(pp[0]) + __uint_as_float(pp[1])) + (__uint_as_float(pp[2]) + __uint_as_float(pp[3]))) +
                                ((__uint_as_float(pp[4]) + __uint_as_float(pp[5])) + (__uint_as_float(pp[6]) + __uint_as_float(pp[7])));
                const uint32_t upd = pack_bf16(bf_round(y) * sg, 0.f);
                STAMP(11);
                mbar_wait(bar0 + 8 * B_ST, 0);
                uint32_t o;
                asm volatile("ld.shared.u16 %0, [%1];" : "=r"(o) : "r"(xo));
                asm volatile("st.global.u16 [%0], %1;" ::"l"(p.out + (size_t)tok * DM + 16 * cl + (lane & 15)), "r"(badd2(o, upd)) : "memory");
            }
            __syncwarp();
            if (elect_one()) mbar_arrive(bar0 + 8 * B_DONE);
        }
        STAMP(10); GSTAMP(15);
    } else {
        asm volatile("setmaxnreg.dec.sync.aligned.u32 %0;" ::"n"(NREG == 168 ? 40 : 384 - 2 * NREG));
        const int q = warp - 12;
        sts32(sb + OFF_MISC + 16 + 4 * q, clk());
        const uint32_t t0 = __shfl_sync(0xffffffffu, lds32v(sb + OFF_MISC + 16 + 4 * q), 0);
        STAMP(0);
        if (q == 1) GSTAMP(14);
        const bool one = elect_one();
        const uint32_t rbar = bar0 + 8 * (B_ROW + q);
        if (one) {
            asm volatile("prefetch.tensormap [%0];" ::"l"(&maps.rows) : "memory");
            mbar_init(rbar, 1);
            if (q == 3) mbar_init(bar0 + 8 * B_WR, 1);
            fence_async();
            mbar_expect_tx(rbar, 8192);
            if (q == 3) {
                mbar_expect_tx(bar0 + 8 * B_WR, 2048);
                bulk_g2s(sb + OFF_GP, p.wr, 2048, bar0 + 8 * B_WR);
            }
        }
        __syncwarp();
        cluster_arrive();
        wait_until(t0 + ROW_DELAY + q * ROW_PERIOD);
        if (one) {
            tma_load_3d(sb + OFF_ROWS + 8192 * q, &maps.rows, 16 * b, 4 * q, rbar);
            asm volatile("prefetch.tensormap [%0];" ::"l"(&maps.u + q) : "memory");
        }
        __syncwarp();
        cluster_wait();
        cluster_arrive();
        STAMP(1);
        wait_until(t0 + X_DELAY + q * X_PERIOD);
        if (one) tma_load_4d_both(sb + OFF_X + 8192 * (4 * h + q), &maps.u, 16 * cl, 4 * (4 * h + q), bar0 + 8 * (B_X + 4 * h + q));
        STAMP(2);
        const char* src = (const char*)((b >> 6) ? p.wu : p.wg) + (64 * q + (b & 63)) * 7168 + 128 * lane;
        const uint32_t phase = t0 + PF_START + (b * PF_PERIOD >> 7) + q * PF_PERIOD;
        auto fill = [&](int j, uint32_t due, const CUtensorMap* map, int c0, int c3) {
            const uint32_t bar = bar0 + 8 * (B_FULL + q + 4 * (j & 1));
            wait_until(due);
            mbar_wait(bar + 8 * (B_EMPTY - B_FULL), (j >> 1) & 1);
            if (one) {
                mbar_expect_tx(bar, 8192);
                tma_load_4d(sb + OFF_RING + (q + 4 * (j & 1)) * 8192, map, c0, c3, bar);
            }
            STAMP(3 + (j >> 1));
        };
#pragma unroll 1
        for (int j = 0; j < 4; j++) {
            wait_until(phase + 4 * j * PF_PERIOD);
            asm volatile("prefetch.global.L2 [%0];" ::"l"(src) : "memory");
            if (lane < 24) asm volatile("prefetch.global.L2 [%0];" ::"l"(src + 4096) : "memory");
            src += 256 * 7168;
            STAMP(6);
            if (b < GU_CTAS) fill(j, t0 + LD_START + (q + 4 * j) * LD_PERIOD, &maps.wgu, 32 * b, q + 4 * j);
        }
#pragma unroll 1
        for (int j = 4; j < (q < 3 ? 6 : 5); j++)
            fill(j, phase + 4 * j * PF_PERIOD + (q + 4 * j - 16) * WD_EXTRA, &maps.wd, 64 * (b >> 3), 7 * (b & 7) + q + 4 * j - 16);
        if (q >= 2) mbar_wait_bounded(bar0 + 8 * (B_DONE - 2 + q), 0);
    }
    cluster_wait();
}

typedef CUresult (*EncodeFn)(CUtensorMap*, CUtensorMapDataType, cuuint32_t, void*, const cuuint64_t*, const cuuint64_t*,
                             const cuuint32_t*, const cuuint32_t*, CUtensorMapInterleave, CUtensorMapSwizzle,
                             CUtensorMapL2promotion, CUtensorMapFloatOOBfill);

void make_map(EncodeFn enc, CUtensorMap* m, int rank, const void* ptr, const cuuint64_t (&dims)[5], const cuuint64_t (&str)[4],
              const cuuint32_t (&box)[5], CUtensorMapSwizzle sw, CUtensorMapL2promotion pr) {
    const cuuint32_t es[5] = {1, 1, 1, 1, 1};
    CUresult rc = enc(m, CU_TENSOR_MAP_DATA_TYPE_BFLOAT16, rank, const_cast<void*>(ptr), dims, str, box, es, CU_TENSOR_MAP_INTERLEAVE_NONE, sw, pr,
                      CU_TENSOR_MAP_FLOAT_OOB_FILL_NONE);
    (void)rc;
}

}

extern "C" void kernel_launch(void* const* d_in, const int* in_sizes, int n_in, void* d_out, int out_size) {
    (void)in_sizes; (void)n_in; (void)out_size;
    static EncodeFn enc = nullptr;
    static void* scr = nullptr;
    if (!enc) {
        void* fn = nullptr;
        cudaDriverEntryPointQueryResult q;
        cudaGetDriverEntryPoint("cuTensorMapEncodeTiled", &fn, cudaEnableDefault, &q);
        enc = (EncodeFn)fn;
        cudaGetSymbolAddress(&scr, g_scr);
        cudaFuncSetAttribute(fused_kernel, cudaFuncAttributeMaxDynamicSharedMemorySize, SMEM_BYTES);
    }
    Maps maps;
    const uintptr_t ag = (uintptr_t)d_in[9], au = (uintptr_t)d_in[10];
    const auto noprom = CU_TENSOR_MAP_L2_PROMOTION_NONE, prom = CU_TENSOR_MAP_L2_PROMOTION_L2_128B;
    make_map(enc, &maps.rows, 3, d_in[0], {64, SEQ, 16, 1}, {2048, 128, 0}, {64, 16, 4, 1}, CU_TENSOR_MAP_SWIZZLE_128B, noprom);
    make_map(enc, &maps.u, 4, d_in[0], {DM, 4, 16, 32}, {32768, 2048, 131072}, {16, 4, 16, 4}, CU_TENSOR_MAP_SWIZZLE_32B, noprom);
    make_map(enc, &maps.out, 5, d_out, {DM, 4, 8, 2, 32}, {32768, 2048, 16384, 131072}, {16, 4, 2, 2, 4}, CU_TENSOR_MAP_SWIZZLE_NONE, noprom);
    make_map(enc, &maps.wgu, 4, (const void*)(ag < au ? ag : au), {FF, 64, 2, 16}, {FF * 2, ag < au ? au - ag : ag - au, 64 * FF * 2}, {32, 64, 2, 1},
             CU_TENSOR_MAP_SWIZZLE_64B, prom);
    make_map(enc, &maps.wd, 4, d_in[11], {DM, 64, 1, 56}, {2048, 131072, 131072}, {64, 64, 1, 1}, CU_TENSOR_MAP_SWIZZLE_128B, prom);
    Ptrs p;
    p.u = (const __nv_bfloat16*)d_in[0];
    p.logA = (const __nv_bfloat16*)d_in[1];
    p.Aim = (const __nv_bfloat16*)d_in[2];
    p.Cre = (const __nv_bfloat16*)d_in[3];
    p.Cim = (const __nv_bfloat16*)d_in[4];
    p.ldt = (const __nv_bfloat16*)d_in[5];
    p.dsk = (const __nv_bfloat16*)d_in[6];
    p.wr = (const __nv_bfloat16*)d_in[8];
    p.wg = (const __nv_bfloat16*)d_in[9];
    p.wu = (const __nv_bfloat16*)d_in[10];
    p.out = (__nv_bfloat16*)d_out;
    p.scr = (uint32_t*)scr;
    p.up_first = ag < au ? 0 : 4096;
    p.zero = 0;
    fused_kernel<<<NCTA + 2, NTHR, SMEM_BYTES, cudaStreamPerThread>>>(p, maps);
}
```

```cpp
#include <cuda_runtime.h>
#include <cuda_bf16.h>
#include <cuda_fp16.h>
#include <cuda.h>
#include <stdint.h>

namespace {

constexpr int SEQ = 2048, DM = 1024, NMODE = 128, FF = 3584;
constexpr int NCTA = 128, NTHR = 512;
constexpr int GU_CTAS = 112;

constexpr int OFF_X = 0;
constexpr int OFF_RING = 65536;
constexpr int ROW_PITCH = 2064;
constexpr int OFF_ROWS = OFF_RING + 32768;
constexpr int OFF_XS = OFF_RING + 65536;
constexpr int OFF_PRIV = OFF_XS + 8 * ROW_PITCH;
constexpr int PRIV = 8768;
constexpr int PLANE = 2240;
constexpr int OFF_GP = OFF_PRIV + 8 * PRIV;
constexpr int OFF_LC = OFF_GP + 8192;
constexpr int OFF_BAR = OFF_LC + 2048;
constexpr int OFF_MISC = OFF_BAR + 352;
constexpr int OFF_STAMP = OFF_MISC + 288;
constexpr int SMEM_BYTES = OFF_STAMP;

constexpr int B_X = 0, B_FULL = 8, B_EMPTY = 16, B_RECV = 24, B_XS = 28, B_DONE = 29, B_ST = 30, B_TAG = 31, B_ROW = 32, B_WR = 36, B_KG = 37, B_VT = 38, B_PV = 39;

constexpr int T_DENSE = 4416;
constexpr int T_PATCH = T_DENSE + 2176;
constexpr int T_S4 = T_PATCH + 112;
constexpr int T_S8 = T_S4 + 736;
constexpr int REC = 272;

#define KG_UNROLL 4
constexpr int KGU = KG_UNROLL;
constexpr uint32_t SPIN_LIMIT = 1u << 22;
#define ROW_DELAY 300
#define H_SLEEP 100
#define NPRE 4
#define SEL_SLEEP 40
#define ROW_PERIOD 450
#define X_PERIOD 0
#define FINE 2
#define INC_AT 1
#define NREG 168
#define DN_RUN 5
#define FREG 128
#define DN_PRE 3
#define DN_LAST 0
#define GU_SPLIT 2
#define FIN_A 4
#define FIN_B 12
#define TORD 0
#define CW_EARLY 0
#define WAKE 63
#define LN_DUP 0
#define Y_RESET 1
#define PHG 480
#define X_DELAY 2500
#define PF_START 3300
#define PF_PERIOD 539
#define WD_EXTRA (PF_PERIOD / 7)
#define LD_LAG 300
#define LD_START 5100
#define LD_PERIOD ((PF_START + 16 * PF_PERIOD + LD_LAG - LD_START) / 15)

constexpr int S_STAT = 0;
constexpr int S_KEY = S_STAT + 8192;
constexpr int S_SEL = S_KEY + 2048;
constexpr int S_EPOCH = S_SEL + 128;
constexpr int S_H = S_EPOCH + 32;
constexpr int S_Y = S_H + 2 * GU_CTAS * 128;
constexpr int S_END = S_Y + 64 * 1024;
__device__ __align__(1024) uint32_t g_scr[S_END];

struct Ptrs {
    const __nv_bfloat16 *logA, *Aim, *Cre, *Cim, *ldt, *dsk, *u, *wr;
    uint32_t* scr;
    const __nv_bfloat16 *wg, *wu;
    __nv_bfloat16* out;
    uint32_t up_first;
    uint32_t zero;
};
struct Maps {
    CUtensorMap rows, u, out, wgu, wd;
};

__device__ __forceinline__ uint32_t clk() { uint32_t c; asm volatile("mov.u32 %0, %%clock;" : "=r"(c)); return c; }
#define STAMP(i) do { } while (0)
#define GSTAMP(i) do { } while (0)

template <int N> struct IC { static constexpr int value = N; };

__device__ __forceinline__ uint32_t s_u32(const void* p) { return (uint32_t)__cvta_generic_to_shared(p); }
__device__ __forceinline__ void mbar_init(uint32_t b, uint32_t n) {
    asm volatile("mbarrier.init.shared::cta.b64 [%0], %1;" ::"r"(b), "r"(n) : "memory");
}
__device__ __forceinline__ void mbar_expect_tx(uint32_t b, uint32_t bytes) {
    asm volatile("mbarrier.arrive.expect_tx.shared::cta.b64 _, [%0], %1;" ::"r"(b), "r"(bytes) : "memory");
}
__device__ __forceinline__ void mbar_arrive(uint32_t b) {
    asm volatile("mbarrier.arrive.shared::cta.b64 _, [%0];" ::"r"(b) : "memory");
}
__device__ __forceinline__ void mbar_arrive_peer(uint32_t b_cluster) {
    asm volatile("mbarrier.arrive.relaxed.cluster.shared::cluster.b64 _, [%0];" ::"r"(b_cluster) : "memory");
}
__device__ __forceinline__ void mbar_wait(uint32_t b, uint32_t parity) {
    asm volatile("{\n\t.reg .pred p;\nW:\n\tmbarrier.try_wait.parity.shared::cta.b64 p, [%0], %1;\n\t@!p bra W;\n\t}" ::"r"(b), "r"(parity) : "memory");
}
__device__ __forceinline__ void mbar_wait_bounded(uint32_t b, uint32_t parity) {
    asm volatile("{\n\t.reg .pred p;\n\t.reg .u32 c;\n\tmov.u32 c, 0;\n"
                 "W:\n\tmbarrier.try_wait.parity.shared::cta.b64 p, [%0], %1, 4000;\n\t@p bra D;\n\t"
                 "add.u32 c, c, 1;\n\tsetp.lt.u32 p, c, 1048576;\n\t@p bra W;\n\ttrap;\nD:\n\t}"
                 ::"r"(b), "r"(parity) : "memory");
}
__device__ __forceinline__ bool elect_one() {
    uint32_t p;
    asm volatile("{ .reg .pred P; elect.sync _|P, 0xffffffff; selp.u32 %0, 1, 0, P; }" : "=r"(p));
    return p != 0;
}
__device__ __forceinline__ uint32_t mapa(uint32_t a, uint32_t rank) {
    uint32_t r;
    asm("mapa.shared::cluster.u32 %0, %1, %2;" : "=r"(r) : "r"(a), "r"(rank));
    return r;
}
__device__ __forceinline__ void cluster_arrive() { asm volatile("barrier.cluster.arrive.relaxed.aligned;" ::: "memory"); }
__device__ __forceinline__ void cluster_wait() { asm volatile("barrier.cluster.wait.aligned;" ::: "memory"); }
__device__ __forceinline__ void tma_load_3d(uint32_t dst, const CUtensorMap* m, int c1, int c2, uint32_t bar) {
    asm volatile("cp.async.bulk.tensor.3d.shared::cluster.global.mbarrier::complete_tx::bytes [%0], [%1, {%3, %4, %5}], [%2];"
                 ::"r"(dst), "l"(m), "r"(bar), "r"(0), "r"(c1), "r"(c2) : "memory");
}
__device__ __forceinline__ void tma_load_4d(uint32_t dst, const CUtensorMap* m, int c0, int c3, uint32_t bar) {
    uint64_t pol;
    asm("createpolicy.fractional.L2::evict_first.b64 %0, 1.0;" : "=l"(pol));
    asm volatile("cp.async.bulk.tensor.4d.shared::cluster.global.mbarrier::complete_tx::bytes.L2::cache_hint [%0], [%1, {%3, %5, %5, %4}], [%2], %6;"
                 ::"r"(dst), "l"(m), "r"(bar), "r"(c0), "r"(c3), "r"(0), "l"(pol) : "memory");
}
__device__ __forceinline__ void wait_until(uint32_t t) {
    asm volatile("{\n\t.reg .pred p;\n\t.reg .s32 c;\nW:\n\tmov.u32 c, %%clock;\n\tsub.s32 c, %0, c;\n\tshr.s32 c, c, 2;\n\tsetp.gt.s32 p, c, %1;\n\t"
                 "@p nanosleep.u32 c;\n\t@p bra.uni W;\n\t}" ::"r"(t), "n"(WAKE) : "memory");
}
__device__ __forceinline__ void tma_load_4d_both(uint32_t dst, const CUtensorMap* m, int c0, int c3, uint32_t bar) {
    asm volatile("cp.async.bulk.tensor.4d.shared::cluster.global.mbarrier::complete_tx::bytes.multicast::cluster [%0], [%1, {%3, %6, %6, %4}], [%2], %5;"
                 ::"r"(dst), "l"(m), "r"(bar), "r"(c0), "r"(c3), "h"((uint16_t)3), "r"(0) : "memory");
}
__device__ __forceinline__ void bulk_g2s(uint32_t dst, const void* src, uint32_t bytes, uint32_t bar) {
    asm volatile("cp.async.bulk.shared::cluster.global.mbarrier::complete_tx::bytes [%0], [%1], %2, [%3];"
                 ::"r"(dst), "l"(src), "r"(bytes), "r"(bar) : "memory");
}
__device__ __forceinline__ void fence_async() { asm volatile("fence.proxy.async.shared::cta;" ::: "memory"); }
__device__ __forceinline__ void named_sync(int id, int n) { asm volatile("bar.sync %0, %1;" ::"r"(id), "r"(n) : "memory"); }

__device__ __forceinline__ void ldsm4(uint32_t* r, uint32_t a) {
    asm volatile("ldmatrix.sync.aligned.m8n8.x4.shared.b16 {%0,%1,%2,%3}, [%4];"
                 : "=r"(r[0]), "=r"(r[1]), "=r"(r[2]), "=r"(r[3]) : "r"(a));
}
__device__ __forceinline__ void ldsm4t(uint32_t* r, uint32_t a) {
    asm volatile("ldmatrix.sync.aligned.m8n8.x4.trans.shared.b16 {%0,%1,%2,%3}, [%4];"
                 : "=r"(r[0]), "=r"(r[1]), "=r"(r[2]), "=r"(r[3]) : "r"(a));
}
__device__ __forceinline__ void stsm4t(uint32_t a, const uint32_t* r) {
    asm volatile("stmatrix.sync.aligned.m8n8.x4.trans.shared.b16 [%0], {%1,%2,%3,%4};"
                 ::"r"(a), "r"(r[0]), "r"(r[1]), "r"(r[2]), "r"(r[3]) : "memory");
}
__device__ __forceinline__ uint32_t lds32(uint32_t a) { uint32_t v; asm volatile("ld.shared.u32 %0, [%1];" : "=r"(v) : "r"(a)); return v; }
__device__ __forceinline__ uint32_t lds32v(uint32_t a) { uint32_t v; asm volatile("ld.volatile.shared.u32 %0, [%1];" : "=r"(v) : "r"(a)); return v; }
__device__ __forceinline__ float lds32f(uint32_t a) { float v; asm volatile("ld.shared.f32 %0, [%1];" : "=f"(v) : "r"(a)); return v; }
__device__ __forceinline__ uint2 lds64(uint32_t a) { uint2 v; asm volatile("ld.shared.v2.u32 {%0,%1}, [%2];" : "=r"(v.x), "=r"(v.y) : "r"(a)); return v; }
__device__ __forceinline__ uint4 lds128(uint32_t a) {
    uint4 v; asm volatile("ld.shared.v4.u32 {%0,%1,%2,%3}, [%4];" : "=r"(v.x), "=r"(v.y), "=r"(v.z), "=r"(v.w) : "r"(a)); return v;
}
template <int D> __device__ __forceinline__ void sts16x2(uint32_t a, float x) {
    asm volatile("{ .reg .b16 h; cvt.rn.bf16.f32 h, %1; st.shared.b16 [%0], h; st.shared.b16 [%0 + %2], h; }" ::"r"(a), "f"(x), "n"(D) : "memory");
}
__device__ __forceinline__ void sts32(uint32_t a, uint32_t v) { asm volatile("st.shared.u32 [%0], %1;" ::"r"(a), "r"(v) : "memory"); }
__device__ __forceinline__ void sts64(uint32_t a, uint32_t x, uint32_t y) { asm volatile("st.shared.v2.u32 [%0], {%1,%2};" ::"r"(a), "r"(x), "r"(y) : "memory"); }
__device__ __forceinline__ void sts128(uint32_t a, uint32_t x, uint32_t y, uint32_t z, uint32_t w) {
    asm volatile("st.shared.v4.u32 [%0], {%1,%2,%3,%4};" ::"r"(a), "r"(x), "r"(y), "r"(z), "r"(w) : "memory");
}
__device__ __forceinline__ void sts128f(uint32_t a, const float* c) {
    asm volatile("st.shared.v4.f32 [%0], {%1,%2,%3,%4};" ::"r"(a), "f"(c[0]), "f"(c[1]), "f"(c[2]), "f"(c[3]) : "memory");
}
__device__ __forceinline__ uint2 ldg64(const void* p) {
    uint2 v; asm volatile("ld.global.nc.L1::no_allocate.v2.u32 {%0,%1}, [%2];" : "=r"(v.x), "=r"(v.y) : "l"(p)); return v;
}
__device__ __forceinline__ uint32_t ldg16(const void* p) {
    uint16_t v; asm volatile("ld.global.nc.u16 %0, [%1];" : "=h"(v) : "l"(p)); return v;
}
__device__ __forceinline__ uint32_t ld_relaxed_32(const void* p) {
    uint32_t v; asm volatile("ld.relaxed.gpu.global.u32 %0, [%1];" : "=r"(v) : "l"(p) : "memory"); return v;
}
__device__ __forceinline__ uint2 ld_relaxed_64(const void* p) {
    uint2 v; asm volatile("ld.relaxed.gpu.global.v2.u32 {%0,%1}, [%2];" : "=r"(v.x), "=r"(v.y) : "l"(p) : "memory"); return v;
}
__device__ __forceinline__ uint4 ld_relaxed_128(const void* p) {
    uint4 v; asm volatile("ld.relaxed.gpu.global.v4.u32 {%0,%1,%2,%3}, [%4];" : "=r"(v.x), "=r"(v.y), "=r"(v.z), "=r"(v.w) : "l"(p) : "memory"); return v;
}
__device__ __forceinline__ void st_relaxed_32(void* p, uint32_t v) {
    asm volatile("st.relaxed.gpu.global.u32 [%0], %1;" ::"l"(p), "r"(v) : "memory");
}
__device__ __forceinline__ void st_relaxed_128(void* p, uint32_t x, uint32_t y, uint32_t z, uint32_t w) {
    asm volatile("st.relaxed.gpu.global.v4.u32 [%0], {%1,%2,%3,%4};" ::"l"(p), "r"(x), "r"(y), "r"(z), "r"(w) : "memory");
}
__device__ __forceinline__ void st_relaxed_64(void* p, uint32_t x, uint32_t y) {
    asm volatile("st.relaxed.gpu.global.u64 [%0], %1;" ::"l"(p), "l"((unsigned long long)x | ((unsigned long long)y << 32)) : "memory");
}
__device__ __forceinline__ void mma_bf16(float* c, uint32_t a0, uint32_t a1, uint32_t a2, uint32_t a3, uint32_t b0, uint32_t b1) {
    asm("mma.sync.aligned.m16n8k16.row.col.f32.bf16.bf16.f32 {%0,%1,%2,%3}, {%4,%5,%6,%7}, {%8,%9}, {%0,%1,%2,%3};"
                 : "+f"(c[0]), "+f"(c[1]), "+f"(c[2]), "+f"(c[3]) : "r"(a0), "r"(a1), "r"(a2), "r"(a3), "r"(b0), "r"(b1));
}
__device__ __forceinline__ void mma_bf16v(float* c, const uint32_t* a, uint32_t b0, uint32_t b1) {
    asm volatile("mma.sync.aligned.m16n8k16.row.col.f32.bf16.bf16.f32 {%0,%1,%2,%3}, {%4,%5,%6,%7}, {%8,%9}, {%0,%1,%2,%3};"
                 : "+f"(c[0]), "+f"(c[1]), "+f"(c[2]), "+f"(c[3]) : "r"(a[0]), "r"(a[1]), "r"(a[2]), "r"(a[3]), "r"(b0), "r"(b1));
}
__device__ __forceinline__ void mma_bf16_z(float* c, uint32_t a0, uint32_t a1, uint32_t a2, uint32_t a3, uint32_t b0, uint32_t b1) {
    asm("mma.sync.aligned.m16n8k16.row.col.f32.bf16.bf16.f32 {%0,%1,%2,%3}, {%4,%5,%6,%7}, {%8,%9}, {%10,%10,%10,%10};"
        : "=f"(c[0]), "=f"(c[1]), "=f"(c[2]), "=f"(c[3]) : "r"(a0), "r"(a1), "r"(a2), "r"(a3), "r"(b0), "r"(b1), "f"(0.f));
}
__device__ __forceinline__ void mma_f16(float* c, const uint4& a, uint32_t b0, uint32_t b1) {
    asm("mma.sync.aligned.m16n8k16.row.col.f32.f16.f16.f32 {%0,%1,%2,%3}, {%4,%5,%6,%7}, {%8,%9}, {%0,%1,%2,%3};"
                 : "+f"(c[0]), "+f"(c[1]), "+f"(c[2]), "+f"(c[3]) : "r"(a.x), "r"(a.y), "r"(a.z), "r"(a.w), "r"(b0), "r"(b1));
}
__device__ __forceinline__ uint32_t pack_bf16(float lo, float hi) {
    uint32_t r; asm("cvt.rn.bf16x2.f32 %0, %1, %2;" : "=r"(r) : "f"(hi), "f"(lo)); return r;
}
__device__ __forceinline__ uint32_t pack_bf16v(float lo, float hi) {
    uint32_t r; asm("cvt.rn.satfinite.bf16x2.f32 %0, %1, %2;" : "=r"(r) : "f"(hi), "f"(lo)); return r;
}
__device__ __forceinline__ uint32_t pack_f16(float lo, float hi) {
    uint32_t r; asm("cvt.rn.f16x2.f32 %0, %1, %2;" : "=r"(r) : "f"(hi), "f"(lo)); return r;
}
__device__ __forceinline__ float bf_lo(uint32_t v) { return __uint_as_float(v << 16); }
__device__ __forceinline__ float bf_hi(uint32_t v) { return __uint_as_float(v & 0xffff0000u); }
__device__ __forceinline__ float bf_round(float x) { return __uint_as_float(pack_bf16(0.f, x)); }
__device__ __forceinline__ __nv_bfloat162 as_b2(uint32_t x) { return *reinterpret_cast<__nv_bfloat162*>(&x); }
__device__ __forceinline__ uint32_t as_u(__nv_bfloat162 x) { return *reinterpret_cast<uint32_t*>(&x); }
__device__ __forceinline__ uint32_t badd2(uint32_t a, uint32_t b) { uint32_t r; asm("add.rn.bf16x2 %0, %1, %2;" : "=r"(r) : "r"(a), "r"(b)); return r; }
__device__ __forceinline__ float rcpf(float x) { float r; asm("rcp.approx.ftz.f32 %0, %1;" : "=f"(r) : "f"(x)); return r; }
__device__ __forceinline__ float sqrtaf(float x) { float r; asm("sqrt.approx.ftz.f32 %0, %1;" : "=f"(r) : "f"(x)); return r; }
__device__ __forceinline__ float ex2f(float x) { float r; asm("ex2.approx.ftz.f32 %0, %1;" : "=f"(r) : "f"(x)); return r; }
constexpr float L2E = 1.4426950408889634f;
constexpr uint32_t ONES = 0x3f803f80u;

__device__ __forceinline__ uint2 recip2(uint32_t s2) {
    const uint32_t hi = pack_bf16(rcpf(bf_lo(s2)), rcpf(bf_hi(s2)));
    return make_uint2(hi, as_u(__hmul2(__hfma2(__hneg2(as_b2(s2)), as_b2(hi), as_b2(ONES)), as_b2(hi))));
}
__device__ __forceinline__ uint32_t normalize2(uint32_t x, __nv_bfloat162 m, __nv_bfloat162 rh, __nv_bfloat162 rl) {
    const __nv_bfloat162 d = __hsub2(as_b2(x), m);
    return as_u(__hfma2(d, rh, __hmul2(d, rl)));
}

__device__ __forceinline__ uint32_t unorder_key(uint32_t k16) { return k16 ^ ((k16 & 0x8000u) ? 0x8000u : 0xffffu); }

struct cplx { float r, i; };
__device__ __forceinline__ cplx csq(cplx a) { return {a.r * a.r - a.i * a.i, (a.r + a.r) * a.i}; }
__device__ __forceinline__ cplx csq_conj(cplx a) { return {a.r * a.r - a.i * a.i, (-a.r - a.r) * a.i}; }
__device__ __forceinline__ cplx cexpp(float a2, float th) {
    float m = ex2f(a2), s, c;
    __sincosf(th, &s, &c);
    return {m * c, m * s};
}
struct hc { __half2 r, i; };
__device__ __forceinline__ __half2 as_h2(uint32_t x) { return *reinterpret_cast<__half2*>(&x); }
__device__ __forceinline__ uint32_t as_u(__half2 x) { return *reinterpret_cast<uint32_t*>(&x); }
__device__ __forceinline__ hc hmul(hc a, hc b) {
    return {__hfma2(a.r, b.r, __hneg2(__hmul2(a.i, b.i))), __hfma2(a.r, b.i, __hmul2(a.i, b.r))};
}
__device__ __forceinline__ hc hpack(cplx a, cplx b) { return {as_h2(pack_f16(a.r, b.r)), as_h2(pack_f16(a.i, b.i))}; }
__device__ __forceinline__ void st_pair(uint32_t a, hc x, hc y) { sts128(a, as_u(x.r), as_u(x.i), as_u(y.r), as_u(y.i)); }
__device__ __forceinline__ void st_quad(uint32_t a, hc x, hc y) { sts128(a, as_u(x.r), as_u(y.r), as_u(x.i), as_u(y.i)); }

#define KSTAMP(i, dep) do { } while (0)
__device__ __forceinline__ void kgen_mma(float (&acc)[5][4], uint32_t priv, int lane, uint2 la, uint2 aim, uint2 cre, uint2 cim, float dt, uint32_t cs2) {
    const int g = lane >> 2, t = lane & 3;
#pragma unroll
    for (int i = 0; i < 5; i++) { acc[i][0] = acc[i][1] = acc[i][2] = acc[i][3] = 0.f; }
    const uint32_t wr = priv + lane * REC, rd = priv + 2 * t * REC;
    const float ndl = -dt * L2E;
#pragma unroll 1
    for (int ps = 0; ps < 2; ps++) {
        const uint32_t lw = ps ? la.y : la.x, iw = ps ? aim.y : aim.x;
        const uint32_t crw = as_u(__hmul2(as_b2(ps ? cre.y : cre.x), as_b2(cs2))), ciw = as_u(__hmul2(as_b2(ps ? cim.y : cim.x), as_b2(cs2)));
        const uint32_t ap = pack_bf16(ex2f(bf_lo(lw) * L2E), ex2f(bf_hi(lw) * L2E));
        const float a2[2] = {bf_lo(ap) * ndl, bf_hi(ap) * ndl}, th[2] = {bf_lo(iw) * dt, bf_hi(iw) * dt};
        cplx p1[2], p2[2], p4[2], p8[2], p32[2], p64[2], p128[2], p256[2], p512[2];
#pragma unroll
        for (int i = 0; i < 2; i++) {
            p1[i] = cexpp(a2[i], th[i]); p32[i] = cexpp(a2[i] * 32.f, th[i] * -32.f);
            p2[i] = csq(p1[i]); p4[i] = csq(p2[i]); p8[i] = csq_conj(p4[i]);
            p64[i] = csq(p32[i]); p128[i] = csq_conj(p64[i]); p256[i] = csq(p128[i]); p512[i] = csq(p256[i]);
        }
        const hc C = {as_h2(pack_f16(bf_lo(crw), bf_hi(crw))), as_h2(pack_f16(bf_lo(ciw), bf_hi(ciw)))};
        const hc z1 = hpack(p1[0], p1[1]), z2 = hpack(p2[0], p2[1]), z4 = hpack(p4[0], p4[1]);
        const hc y8 = hpack(p8[0], p8[1]), y32 = hpack(p32[0], p32[1]), y64 = hpack(p64[0], p64[1]);
        const hc z128 = hpack(p128[0], p128[1]), z256 = hpack(p256[0], p256[1]), z512 = hpack(p512[0], p512[1]);
        KSTAMP(8 + 3 * ps, z512.r);
        __syncwarp();
        const hc c1 = hmul(C, z1), c2 = hmul(C, z2), c5 = hmul(c1, z4), c6 = hmul(c2, z4);
        st_pair(wr + 160, hmul(c1, z128), hmul(c2, z128));
        st_pair(wr + 128, c1, c2);
        st_pair(wr + 176, hmul(c5, z128), hmul(c6, z128));
        st_pair(wr + 144, c5, c6);
        const hc y16 = hmul(y8, y8), y48 = hmul(y16, y32), y24 = hmul(y16, y8), y40 = hmul(y32, y8), y56 = hmul(y48, y8), y72 = hmul(y64, y8);
        st_quad(wr, {as_h2(0x3c003c00u), as_h2(0u)}, y8);
        st_quad(wr + 80, hmul(y64, y16), hmul(y64, y24));
        st_quad(wr + 16, y16, y24);
        st_quad(wr + 96, hmul(y64, y32), hmul(y64, y40));
        st_quad(wr + 32, y32, y40);
        st_quad(wr + 112, hmul(y64, y48), hmul(y64, y56));
        st_quad(wr + 48, y48, y56);
        st_quad(wr + 64, y64, y72);
        const hc z258 = hmul(z256, z2);
        st_pair(wr + 192, hmul(z256, z1), z258);
        st_pair(wr + 224, z2, hmul(z512, z4));
        st_pair(wr + 240, z2, hmul(z512, z512));
        st_pair(wr + 208, z258, z512);
        KSTAMP(9 + 3 * ps, z512.r);
        __syncwarp();
#pragma unroll KGU
        for (int k2 = 0; k2 < 4; k2++) {
#pragma unroll
            for (int s = 0; s < 2; s++) {
                const uint32_t o = rd + k2 * 8 * REC + s * REC;
                const uint4 A = lds128(o + 16 * g);
                const uint2 h = lds64(o + 128 + 8 * g);
                const uint4 M = lds128(o + 192 + 16 * (g & 1)), N = lds128(o + 224 + 8 * (g & 2));
                const hc H0 = {as_h2(h.x), as_h2(h.y)};
                const hc H1 = hmul(H0, {as_h2(N.x), as_h2(N.y)}), H2 = hmul(H0, {as_h2(M.x), as_h2(M.y)});
                const hc H3 = hmul(H2, {as_h2(M.z), as_h2(M.w)}), H4 = hmul(H3, {as_h2(N.z), as_h2(N.w)});
                mma_f16(acc[0], A, h.x, h.y);
                mma_f16(acc[1], A, as_u(H1.r), as_u(H1.i));
                mma_f16(acc[2], A, as_u(H2.r), as_u(H2.i));
                mma_f16(acc[3], A, as_u(H3.r), as_u(H3.i));
                mma_f16(acc[4], A, as_u(H4.r), as_u(H4.i));
            }
        }
        KSTAMP(10 + 3 * ps, z512.r);
    }
}

__device__ __forceinline__ void kgen_tables(const float (&acc)[5][4], uint32_t priv, int lane, float scale, float k0) {
    const int g = lane >> 2, t0 = lane & 1, t1 = (lane >> 1) & 1;
    __syncwarp();
    sts128(priv + 16 * lane + (lane < 17 ? T_PATCH - 48 : T_S4 + 608 - 272), 0, 0, 0, 0);
    if (lane < 20) sts128(priv + 16 * lane + (lane < 8 ? 0 : lane < 16 ? PLANE - 128 : T_DENSE - 256), 0, 0, 0, 0);
    uint32_t w2[2], w3[2], w4[2], ab[2], W[2], pv[2];
#pragma unroll
    for (int hf = 0; hf < 2; hf++) {
        const float k1 = acc[0][2 * hf] * scale, k2 = acc[0][2 * hf + 1] * scale, k3 = acc[1][2 * hf] * scale, k4 = acc[1][2 * hf + 1] * scale;
        w2[hf] = pack_bf16(k2, k1); w3[hf] = pack_bf16(k3, k2); w4[hf] = pack_bf16(k4, k3);
        ab[hf] = pack_bf16(acc[2][2 * hf + 1] * scale, acc[2][2 * hf] * scale);
        W[hf] = __byte_perm(w4[hf], ab[hf], 0x5410);
    }
    pv[1] = __shfl_xor_sync(0xffffffffu, t0 ? W[0] : W[1], 1);
    pv[0] = __shfl_sync(0xffffffffu, t0 ? W[1] : W[0], t0 ? lane - 1 : lane < 4 ? 31 - lane : lane - 3);
    const uint32_t kk = pack_bf16(k0, 0.f);
    if (lane == 0) pv[0] = __byte_perm(kk, pv[0], 0x5410);
    const uint32_t pd = priv + T_DENSE + 64 + 512 * t1 + 64 * g + 16 * t0;
#pragma unroll
    for (int hf = 0; hf < 2; hf++) {
        sts128(pd + 32 * hf, __byte_perm(w2[hf], pv[hf], 0x5432), w2[hf], w3[hf], w4[hf]);
        sts128(pd + 32 * hf + 1024, __byte_perm(pv[hf], 0, 0x3232), __byte_perm(ab[hf], pv[hf], 0x7632), ab[hf], __byte_perm(ab[hf], 0, 0x1010));
    }
    __syncwarp();
    if (lane == 31) {
        const uint32_t aa = __byte_perm(ab[1], 0, 0x1010);
        sts32(priv + T_DENSE + 60, kk);
        sts128(priv + T_PATCH - 64, aa, aa, aa << 16, 0u);
    }
}
__device__ __forceinline__ void kgen_tables2(const float (&acc)[5][4], uint32_t priv, int lane, float scale) {
    const int g = lane >> 2, t0 = lane & 1, t1 = (lane >> 1) & 1;
    const uint32_t p4 = priv + T_S4 + 16 * (6 + g + 8 * t1) + 4 * (t0 ^ 1), p8 = priv + T_S8 + 8 * (6 + g + 8 * t1 + 32 * t0);
#pragma unroll
    for (int i = 0; i < 4; i++) {
        sts16x2<18>(p4 + 256 * (i & 1) + 8 * (i >> 1), acc[3][i] * scale);
        sts16x2<10>(p8 + 128 * (i & 1) + 4 * (i >> 1), acc[4][i] * scale);
    }
    if (lane == 31) {
        const uint32_t c3 = pack_bf16(acc[3][3] * scale, 0.f);
        sts128(priv + T_PATCH + 48, c3, c3 * 0x10001u, c3 << 16, 0u);
    }
    __syncwarp();
}

__device__ __forceinline__ void ld_frag(uint32_t (&T)[4], uint32_t q) { T[0] = lds32(q); T[1] = lds32(q + 32); T[2] = lds32(q - 32); T[3] = lds32v(q); }
__device__ __forceinline__ void ld_swap(uint32_t (&T)[4], uint32_t q) { T[2] = lds32v(q); T[3] = lds32v(q + 32); T[0] = lds32v(q - 32); T[1] = lds32v(q); }
__device__ __forceinline__ void add_frag(uint32_t (&S)[4], const uint32_t (&E)[4], const uint32_t (&O)[4]) {
    S[0] = badd2(E[0], O[1]); S[1] = badd2(E[1], O[3]); S[2] = badd2(E[2], O[0]); S[3] = badd2(E[3], O[2]);
}
__device__ __forceinline__ void mma4(float* c, const uint32_t (&a)[4], uint32_t b0, uint32_t b1, bool first = false) {
    if (first) mma_bf16_z(c, a[0], a[1], a[2], a[3], b0, b1);
    else mma_bf16(c, a[0], a[1], a[2], a[3], b0, b1);
}
template <bool FIRST>
__device__ __forceinline__ void dense_step(float (&acc)[16][4], float (&B)[8][4], uint32_t (&T0)[4], uint32_t (&T1)[4], uint32_t (&R)[8][4],
                                           uint32_t pq, uint32_t va) {
    uint32_t T2[4], T3[4], S[4], s[8][2];
#pragma unroll
    for (int i = NPRE; i < 8; i++) ldsm4(R[i], va + i * 256);
    ld_frag(T2, pq + 1024); ld_swap(T3, pq + 1536);
    add_frag(S, T0, T1);
#pragma unroll
    for (int i = 0; i < 8; i++) {
        s[i][0] = badd2(R[i][0], R[i][3]); s[i][1] = badd2(R[i][1], R[i][2]);
        mma4(acc[2 * i], T0, R[i][0], R[i][1], FIRST);
        mma4(B[i], T1, R[i][2], R[i][3], FIRST);
        mma4(acc[2 * i + 1], S, s[i][0], s[i][1], FIRST);
    }
    ld_frag(T0, pq - 64); ld_swap(T1, pq + 448);
    add_frag(S, T2, T3);
#pragma unroll
    for (int i = 0; i < 7; i++) {
        if (!FIRST || i) mma4(acc[2 * i + 2], T2, R[i][0], R[i][1]);
        mma4(B[i + 1], T3, R[i][2], R[i][3]);
        mma4(acc[2 * i + 3], S, s[i][0], s[i][1]);
        if (i < NPRE) ldsm4(R[i], va + 16 + i * 256);
    }
}
template <class Wait, class After>
__device__ __forceinline__ void dense_phase(float (&acc)[16][4], uint32_t priv, int lane, Wait wait_for_tokens, After after_loop) {
    const int m = lane >> 3, r = lane & 7;
    const uint32_t pb = priv + T_DENSE + 4 * (15 + (lane >> 2) - 2 * (lane & 3));
    const uint32_t v8 = priv + 128 * (m >> 1) + 16 * r;
    float B[8][4];
    uint32_t T0[4], T1[4], R[8][4];
    uint32_t pq = pb + 512, va = v8 + PLANE * ((m ^ (m >> 1)) & 1);
    ld_frag(T0, pq); ld_swap(T1, pq + 512);
    wait_for_tokens();
#pragma unroll
    for (int i = 0; i < NPRE; i++) ldsm4(R[i], va + i * 256);
    dense_step<true>(acc, B, T0, T1, R, pq, va);
#pragma unroll 1
    do {
        pq -= 64; va += 16;
        dense_step<false>(acc, B, T0, T1, R, pq, va);
    } while (pq != pb + 64);
    after_loop();
    KSTAMP(14, as_h2(0u));
    const uint32_t pp = pb + T_PATCH - T_DENSE - 24;
    uint32_t N0[4], N1[4];
    ld_swap(T1, pb); ld_frag(N0, pp); ld_swap(N1, pp);
#pragma unroll
    for (int i = NPRE; i < 8; i++) ldsm4(R[i], va + 16 + i * 256);
#pragma unroll
    for (int i = 0; i < 8; i++)
#pragma unroll
        for (int j = 0; j < 4; j++) {
            acc[2 * i + 1][j] = (acc[2 * i + 1][j] - acc[2 * i][j]) - B[i][j];
            if (i) acc[2 * i][j] += B[i - 1][j];
        }
#pragma unroll
    for (int i = 0; i < 8; i++) {
        mma4(acc[2 * i], T0, R[i][0], R[i][1]);
        mma4(acc[2 * i + 1], T1, R[i][2], R[i][3]);
        if (i >= 4) {
            mma4(acc[2 * i], N0, R[i - 4][0], R[i - 4][1]);
            mma4(acc[2 * i + 1], N1, R[i - 4][2], R[i - 4][3]);
        }
    }
    const uint32_t b = v8 + PLANE + 112;
    const uint32_t bz = (m & 1) ? priv : b, bm = (m & 1) ? b : b + 512;
    const uint32_t M[4] = {lds32(pb + 4 * 520), lds32(pb + 4 * 528), lds32v(pp + 32), lds32(pp + 64)};
#pragma unroll
    for (int i = 0; i < 6; i++) {
        uint32_t V[4];
        ldsm4(V, i < 2 ? bz + ((m & 1) ? 0 : i * 256) : bm + (i - 2) * 256);
        mma4(acc[2 * i + 4], M, V[0], V[1]);
        mma4(acc[2 * i + 5], M, V[2], V[3]);
    }
}

__device__ __forceinline__ uint32_t ones2(int c, int lo, int n) {
    return (((uint32_t)(c - lo) < (uint32_t)n) ? 0x3f80u : 0u) | (((uint32_t)(c + 1 - lo) < (uint32_t)n) ? 0x3f800000u : 0u);
}
template <int L1, int N1, int L2, int N2, int D>
__device__ __forceinline__ void box_ones(uint32_t dst, int d) { sts128(dst, ones2(d, L1, N1), ones2(d, L2, N2), ones2(d + D, L1, N1), ones2(d + D, L2, N2)); }
__device__ __forceinline__ uint32_t tok_at(int T) { return PLANE * ((T >> 3) & 1) + 16 * ((T >> 4) + 8) + 2 * (T & 7); }
__device__ __forceinline__ float left_col(float cur, float prev, int lane) {
    return __shfl_sync(0xffffffffu, (lane & 3) == 3 ? prev : cur, lane + 3, 4);
}
struct Tails {
    uint4 q4, q8, B4[5], ad;
    uint2 B8[8];
    uint32_t W[2][4], A[2][2][4];
    float p1, p3, p8;
    static __host__ __device__ constexpr bool is8(int k) { return k >= 4 && (TORD ? (k & 1) : (k & 4) == 0); }
    static __host__ __device__ constexpr int grp(int k) { return k < 4 ? k : TORD ? (k - 4) / 2 + (is8(k) ? 0 : 4) : (k & 3) + 4 * ((k - 4) >> 3) + (is8(k) ? 0 : 4); }
    __device__ __forceinline__ void load(int k, uint32_t priv) {
        uint32_t* w = W[k & 1];
        const uint32_t o = priv + 128 * grp(k);
        if (is8(k)) {
            const uint2 vy = lds64(o + ad.w), vx = lds64(o + ad.z);
            w[0] = vy.x; w[1] = vy.y; w[2] = vx.x; w[3] = vx.y;
        } else { w[0] = lds32(o + ad.y); w[1] = lds32(o + ad.x + 16); w[2] = lds32(o + ad.x); w[3] = lds32v(o + ad.y); }
    }
    __device__ __forceinline__ void box(int k, int lane) {
        const uint32_t* w = W[k & 1];
        const uint4 q = is8(k) ? q8 : q4;
        uint32_t (&a)[2][4] = A[k & 1];
        float X[4], Y[4];
        mma_bf16_z(Y, q.x, q.y, q.z, q.w, w[0], w[1]);
        mma_bf16_z(X, q.x, q.y, q.z, q.w, w[2], w[3]);
        a[0][0] = pack_bf16(X[0], X[1]); a[0][1] = pack_bf16(Y[0], Y[1]);
        if (is8(k)) {
            a[0][2] = pack_bf16(left_col(Y[3], p8, lane), Y[2]); a[0][3] = pack_bf16(X[2], X[3]);
            p8 = Y[3];
        } else {
            a[0][2] = pack_bf16(X[2], X[3]); a[0][3] = pack_bf16(Y[2], Y[3]);
            a[1][0] = pack_bf16(left_col(Y[1], p1, lane), Y[0]); a[1][1] = pack_bf16v(X[0], X[1]);
            a[1][2] = pack_bf16(left_col(Y[3], p3, lane), Y[2]); a[1][3] = pack_bf16v(X[2], X[3]);
            p1 = Y[1]; p3 = Y[3];
        }
    }
    __device__ __forceinline__ void taps(int k, float (&acc)[16][4]) {
        const int G = grp(k);
        if (is8(k)) {
#pragma unroll
            for (int b = 0; b < 8; b++) if (G + 8 + b < 16) mma4(acc[G + 8 + b], A[k & 1][0], B8[b].x, B8[b].y);
        } else {
#pragma unroll
            for (int b = 0; b < 5; b++) if (G + 4 + b < 16) mma4(acc[G + 4 + b], A[k & 1][0], B4[b].x, B4[b].y);
#pragma unroll
            for (int b = 0; b < 5; b++) if (G + 4 + b < 16) mma4(acc[G + 4 + b], A[k & 1][1], B4[b].z, B4[b].w);
        }
    }
    __device__ __forceinline__ void start(uint32_t lc, uint32_t priv, uint32_t tap, int lane) {
        ad = lds128(lc + 1024); q4 = lds128(lc); q8 = lds128(lc + 512);
        p1 = p3 = p8 = 0.f;
        load(0, priv); load(1, priv);
#pragma unroll
        for (int i = 0; i < 5; i++) B4[i] = lds128(priv + T_S4 + 128 * i + 2 * tap);
        box(0, lane);
    }
    template <int K0, int K1>
    __device__ __forceinline__ void run(float (&acc)[16][4], uint32_t priv, uint32_t tap, int lane) {
#pragma unroll
        for (int k = K0; k < K1; k++) {
            if (k + 2 < 20) load(k + 2, priv);
            if (k == 4) {
#pragma unroll
                for (int i = 0; i < 8; i++) B8[i] = lds64(priv + T_S8 + 64 * i + tap);
            }
            if (k + 1 < 20) box(k + 1, lane);
            taps(k, acc);
        }
    }
};
__device__ __forceinline__ void lane_consts(uint32_t dst, int unit, int lane) {
    const int g = lane >> 2, t = lane & 3, m = lane >> 3, r = lane & 7;
    if (unit == 0) box_ones<0, 5, 5, 3, 8>(dst, 2 * t - g);
    else if (unit == 1) box_ones<1, 7, 0, 9, 2>(dst, 4 * t - g);
    else if (unit == 2) sts128(dst, tok_at(16 * g - 10 + 2 * t), tok_at(16 * g - 2 + 2 * t), tok_at(16 * g - 12 + 4 * t), tok_at(16 * g - 4 + 4 * t));
    else {
        const uint32_t low = 64 * (t >> 1) + 32 * (g & 1) + 16 * (t & 1), hi = (lane & 24) + (lane & 16);
        sts128(dst, 128 * hi + low, 512 * (4 * (r & 2) + 2 * m + (r & 1)) + 16 * ((r >> 2) ^ (2 * (r & 3))), 32 * hi + low, 8 * (6 + g - 2 * t));
    }
}

__device__ __forceinline__ uint32_t mean_std(float mu, float var) { return pack_bf16(mu, sqrtaf(bf_round(bf_round(var) + 1e-5f))); }
__device__ __noinline__ uint2 ln_centred(uint32_t sb, float mu) {
    const int lane = threadIdx.x & 31;
    uint32_t ms = 0;
    float res = 0.f, ri = 0.f;
#pragma unroll 1
    for (int mode = 0; mode < 2; mode++) {
#pragma unroll 1
        for (int rr = 0; rr < 16; rr++) {
            const float c0 = __shfl_sync(0xffffffffu, mu, rr), rj = __shfl_sync(0xffffffffu, ri, rr);
            float c = 0.f;
#pragma unroll 1
            for (int k = 0; k < 16; k++) {
                const uint32_t q = lds32(sb + OFF_ROWS + k * 2048 + rr * 128 + ((lane * 4) ^ ((rr & 7) << 4))), wq = lds32(sb + OFF_GP + k * 128 + lane * 4);
                const float d0 = bf_lo(q) - c0, d1 = bf_hi(q) - c0;
                if (mode) c = fmaf(bf_round(bf_round(d0) * rj), bf_lo(wq), fmaf(bf_round(bf_round(d1) * rj), bf_hi(wq), c));
                else c = fmaf(d0, d0, fmaf(d1, d1, c));
            }
#pragma unroll 1
            for (int o = 16; o; o >>= 1) c += __shfl_xor_sync(0xffffffffu, c, o);
            if ((lane & 15) == rr) res = c;
        }
        if (mode == 0) { ms = mean_std(mu, res * (1.f / DM)); mu = bf_lo(ms); ri = rcpf(bf_hi(ms)); }
    }
    named_sync(1, 128);
    return make_uint2(ms, __float_as_uint(res));
}

__device__ __forceinline__ void router_cta(uint32_t* scr, uint32_t sb, uint32_t zero, int tid, int warp) {
    const int lane = tid & 31;
    const uint32_t cand = sb + 128;
    const uint32_t epoch = ld_relaxed_32(scr + S_EPOCH);
    if (tid < 128) st_relaxed_32(scr + S_SEL + tid, 0u);
    if (tid == 0) sts32(sb + 64, cand);
    sts128(cand + 16 * tid, 0, 0, 0, 0);
    asm volatile("fence.acq_rel.gpu;" ::: "memory");
    const uint32_t tag = (epoch + 1u) | 0x8000u;
    STAMP(0); GSTAMP(1);
    uint32_t* const psel = scr + S_SEL + 32 * (lane & 3);
    const uint32_t cnt = sb + 64 + (tid & zero);
    uint32_t it = 0;
    uint4 q;
#pragma unroll 1
    do {
        q = ld_relaxed_128(scr + S_KEY + 4 * tid);
        if (++it > SPIN_LIMIT) __trap();
    } while (!__all_sync(0xffffffffu, (((q.x ^ tag) | (q.y ^ tag) | (q.z ^ tag) | (q.w ^ tag)) & 0xffffu) == 0));
    STAMP(2);
    uint32_t key[4] = {q.x, q.y, q.z, q.w};
#pragma unroll
    for (int j = 0; j < 4; j++) key[j] = ((key[j] ^ ((uint32_t)((int)key[j] >> 31) | 0x80000000u)) & 0xffff0000u) | (0xffffu - (uint32_t)(4 * tid + j));
    const uint32_t gm = __reduce_max_sync(0xffffffffu, max(max(key[0], key[1]), max(key[2], key[3])));
    sts32(sb + 4 * warp, gm);
    __syncthreads();
    const uint2 pr = lds64(sb + 8 * (lane & 7));
    const uint32_t tau = __reduce_min_sync(0xffffffffu, max(pr.x, pr.y));
    asm volatile("{\n\t.reg .pred p<4>;\n\t.reg .u32 a<4>;\n\t"
                 "setp.ge.u32 p0, %0, %4;\n\tsetp.ge.u32 p1, %1, %4;\n\tsetp.ge.u32 p2, %2, %4;\n\tsetp.ge.u32 p3, %3, %4;\n\t"
                 "@p0 atom.shared.add.u32 a0, [%5], 4;\n\t@p1 atom.shared.add.u32 a1, [%5], 4;\n\t"
                 "@p2 atom.shared.add.u32 a2, [%5], 4;\n\t@p3 atom.shared.add.u32 a3, [%5], 4;\n\t"
                 "@p0 st.shared.u32 [a0], %0;\n\t@p1 st.shared.u32 [a1], %1;\n\t@p2 st.shared.u32 [a2], %2;\n\t@p3 st.shared.u32 [a3], %3;\n\t}"
                 ::"r"(key[0]), "r"(key[1]), "r"(key[2]), "r"(key[3]), "r"(tau), "r"(cnt) : "memory");
    __syncthreads();
    STAMP(6);
    const uint32_t c0 = lds32v(cand + 4 * lane);
    uint2 k = lds64(cand + 8 * warp);
    const uint32_t end = __shfl_sync(0xffffffffu, lds32v(sb + 64), 0);
    uint32_t i = cand + 8 * warp;
#pragma unroll 1
    do {
        uint32_t r0 = __popc(__ballot_sync(0xffffffffu, c0 > k.x)), r1 = __popc(__ballot_sync(0xffffffffu, c0 > k.y));
#pragma unroll 1
        for (uint32_t j = cand + 128; j < end; j += 128) {
            const uint32_t c = lds32(j + 4 * lane);
            r0 += __popc(__ballot_sync(0xffffffffu, c > k.x)); r1 += __popc(__ballot_sync(0xffffffffu, c > k.y));
        }
        const uint32_t rk = (lane & 4) ? r1 : r0;
        if (rk < 8 && lane < 8) st_relaxed_64(psel + 2 * rk, (lane & 4) ? k.y : k.x, tag);
        i += 128;
        k = lds64(i);
    } while (i < end);
    STAMP(4); GSTAMP(5);
    if (tid == 0) st_relaxed_32(scr + S_EPOCH, epoch + 1u);
}

__global__ void __cluster_dims__(2, 1, 1) __launch_bounds__(NTHR, 1)
fused_kernel(const __grid_constant__ Ptrs p, const __grid_constant__ Maps maps) {
    extern __shared__ __align__(1024) unsigned char smem[];
    const uint32_t sb = s_u32(smem);
    const int tid = threadIdx.x, lane = tid & 31;
    const int warp = __shfl_sync(0xffffffffu, tid >> 5, 0);
    const int b = blockIdx.x, h = b & 1, cl = b >> 1;
    const uint32_t bar0 = sb + OFF_BAR;
    const int m = lane >> 3, r = lane & 7;
    if (b >= NCTA) {
        if (b == NCTA) router_cta(p.scr, sb, p.zero, tid, warp);
        return;
    }
    if (warp < 8) {
        const int w = warp, dch = 8 * b + w;
        STAMP(0);
        if (INC_AT == 0) asm volatile("setmaxnreg.inc.sync.aligned.u32 %0;" ::"n"(NREG));
        const int po = dch * NMODE + 4 * lane;
        const uint2 la = ldg64(p.logA + po), aim = ldg64(p.Aim + po), cre = ldg64(p.Cre + po), cim = ldg64(p.Cim + po);
        const uint32_t ldt16 = ldg16(p.ldt + dch), dsk16 = ldg16(p.dsk + dch);
        cluster_arrive();
        if (CW_EARLY) cluster_wait();
        if (INC_AT == 1) asm volatile("setmaxnreg.inc.sync.aligned.u32 %0;" ::"n"(NREG));
        const uint32_t priv = sb + OFF_PRIV + w * PRIV;
        const int g = lane >> 2, t = lane & 3;
        const uint32_t* sp = p.scr + S_STAT + 2048 * (cl & 3) + 256 * w + 16 * t + 2 * g;
        uint2 sq[4];
        float kacc[5][4], kscale;
        {
            const uint32_t m2 = as_u(__hmax2(__hmax2(__habs2(as_b2(cre.x)), __habs2(as_b2(cre.y))), __hmax2(__habs2(as_b2(cim.x)), __habs2(as_b2(cim.y)))));
            const uint32_t eb = min(max(__reduce_max_sync(0xffffffffu, max(m2 << 16, m2)) >> 23, 1u), 252u);
            const float dt = bf_round(ex2f(bf_lo(ldt16) * L2E));
            float s0[4];
            mma_bf16_z(s0, ONES, ONES, ONES, ONES, cre.x, cre.y);
            STAMP(1);
            kgen_mma(kacc, priv, lane, la, aim, cre, cim, dt, (253u - eb) * 0x00800080u);
            STAMP(2);
            if (INC_AT == 2) asm volatile("setmaxnreg.inc.sync.aligned.u32 %0;" ::"n"(NREG));
            if (!CW_EARLY) cluster_wait();
            __syncwarp();
            if (elect_one()) mbar_arrive(bar0 + 8 * B_KG);
#pragma unroll
            for (int i = 0; i < 4; i++) sq[i] = ld_relaxed_64(sp + 64 * i);
            float k0 = s0[0] + s0[1];
            k0 += __shfl_xor_sync(0xffffffffu, k0, 1);
            k0 += __shfl_xor_sync(0xffffffffu, k0, 2);
            kscale = (dt + dt) * __uint_as_float((eb + 1u) << 23);
            kgen_tables(kacc, priv, lane, kscale, fmaf(k0, dt + dt, bf_lo(dsk16) + 1.f));
        }
        STAMP(3);
        {
            mbar_wait(bar0 + 8 * B_TAG, 0);
            const uint32_t want = lds32(sb + OFF_MISC);
            uint32_t s2[4];
#pragma unroll 1
            while (true) {
#pragma unroll
                for (int i = 0; i < 4; i++) s2[i] = __byte_perm(sq[i].x, sq[i].y, 0x7632) ^ want;
                if (__all_sync(0xffffffffu, ((s2[0] | s2[1] | s2[2] | s2[3]) & 0x80008000u) == 0)) break;
#pragma unroll
                for (int i = 0; i < 4; i++) sq[i] = ld_relaxed_64(sp + 64 * i);
            }
            STAMP(4);
            mbar_wait(bar0 + 8 * (B_X + w), 0);
            STAMP(5);
            uint32_t v[8][4];
#pragma unroll
            for (int i = 0; i < 4; i++) {
                const uint2 rc = recip2(s2[i]);
#pragma unroll
                for (int hf = 0; hf < 2; hf++) {
                    const __nv_bfloat162 mm = __low2bfloat162(as_b2(hf ? sq[i].y : sq[i].x));
                    const __nv_bfloat162 rh = hf ? __high2bfloat162(as_b2(rc.x)) : __low2bfloat162(as_b2(rc.x));
                    const __nv_bfloat162 rl = hf ? __high2bfloat162(as_b2(rc.y)) : __low2bfloat162(as_b2(rc.y));
                    const uint4 q = lds128(sb + OFF_X + 8192 * w + 32 * lane + ((h ^ (g & 1)) << 4) + 2048 * i + 1024 * hf);
                    uint32_t* o = v[2 * i + hf];
                    o[0] = normalize2(q.x, mm, rh, rl); o[1] = normalize2(q.y, mm, rh, rl); o[2] = normalize2(q.z, mm, rh, rl); o[3] = normalize2(q.w, mm, rh, rl);
                }
            }
            mbar_wait(bar0 + 8 * B_KG, 0);
            const uint32_t dst = sb + OFF_PRIV + (2 * m + (r & 1)) * PRIV + 128 + 256 * w + 16 * (r >> 1);
#pragma unroll
            for (int i = 0; i < 8; i++) stsm4t(dst + 64 * (i >> 1) + PLANE * (i & 1), v[i]);
            __syncwarp();
            if (elect_one()) { mbar_arrive(bar0 + 8 * B_VT); mbar_arrive_peer(mapa(bar0 + 8 * B_PV, h ^ 1)); }
        }
        if (INC_AT == 3) { __syncwarp(); asm volatile("setmaxnreg.inc.sync.aligned.u32 %0;" ::"n"(NREG)); }
        kgen_tables2(kacc, priv, lane, kscale);
        if (INC_AT == 4) asm volatile("setmaxnreg.inc.sync.aligned.u32 %0;" ::"n"(NREG));
        float acc[16][4];
        dense_phase(acc, priv, lane, [&]() {
            mbar_wait(bar0 + 8 * B_VT, 0);
            STAMP(6);
        }, [&]() { mbar_wait(bar0 + 8 * B_PV, 0); });
        STAMP(7);
        const uint32_t sd = sb + OFF_X + 512 * (8 * h + w) + 16 * (lane ^ (2 * (w & 1) + 4 * h));
        const uint32_t sd0 = mapa(sd + 8192, 0), sd1 = mapa(sd, 1);
        auto send = [&](auto PT) {
            constexpr int pt = decltype(PT)::value;
#pragma unroll
            for (int i = 0; i < 2; i++) {
                const float* c0 = acc[4 * pt + 2 * i];
                const float* c1 = acc[4 * pt + 2 * i + 1];
                asm volatile("st.async.weak.shared::cluster.mbarrier::complete_tx::bytes.v4.b32 [%0 + %6], {%1,%2,%3,%4}, [%5];"
                             ::"r"(i ? sd1 : sd0), "r"(pack_bf16(c0[0], c0[1])), "r"(pack_bf16(c0[2], c0[3])), "r"(pack_bf16(c1[0], c1[1])),
                               "r"(pack_bf16(c1[2], c1[3])), "r"(mapa(bar0 + 8 * (B_RECV + pt), i)), "n"(16384 * pt) : "memory");
            }
        };
        const uint4 lc = lds128(sb + OFF_LC + 1536 + 16 * lane);
        const uint32_t stg = (priv + T_DENSE + 63) & ~127u, so = stg + lc.z;
        const uint32_t xa = sb + OFF_X + 16384 * (w >> 2) + 8192 * h + 256 * (w & 3) + lc.x;
        const uint32_t sa = sb + OFF_X + 16384 * (w >> 2) + 8192 * (h ^ 1) + 128 * (w & 3) + lc.y;
        constexpr int ST2 = -2048;
        auto finish = [&](int ph) {
            if (ph == FINE) STAMP(1);
            const int box = 4 * ph + 2 * (w >> 2) + h;
            uint4 x[4];
            uint32_t s[4][4];
#pragma unroll
            for (int i = 0; i < 4; i++) x[i] = lds128((xa ^ (8 * (i & 2))) + 32768 * ph + 2048 * (i & 1) + 64 * (i & 2));
            if (ph == FINE) STAMP(2);
            mbar_wait(bar0 + 8 * (B_RECV + 2 * ph + (w >> 2)), 0);
            if (ph == FINE) STAMP(3);
            const uint32_t routed = __shfl_sync(0xffffffffu, lds32(sb + OFF_MISC + 4), 0);
#pragma unroll
            for (int i = 0; i < 4; i++) ldsm4t(s[i], (sa ^ (32 * i)) + 32768 * ph);
#pragma unroll
            for (int i = 0; i < 4; i++) { s[i][0] = badd2(x[i].x, s[i][0]); s[i][1] = badd2(x[i].y, s[i][1]); s[i][2] = badd2(x[i].z, s[i][2]); s[i][3] = badd2(x[i].w, s[i][3]); }
            if (ph == FINE) STAMP(4);
            if ((routed >> (4 * box + (w & 3))) & 1) {
                const uint32_t tk = 256 * box + 128 * (g >> 2) + 32 * (t >> 1) + 16 * (g & 1) + 4 * (g & 2) + 2 * (w & 3);
                const uint32_t mk[2] = {lds32(sb + OFF_MISC + 32 + 4 * (tk >> 5)) >> (tk & 31), lds32(sb + OFF_MISC + 40 + 4 * (tk >> 5)) >> (tk & 31)};
                __nv_bfloat16* o = p.out + (size_t)tk * DM + 16 * cl + 8 * (t & 1);
#pragma unroll
                for (int i = 0; i < 4; i++)
                    asm volatile("{\n\t.reg .pred p;\n\tsetp.eq.u32 p, %6, 0;\n\t@!p st.shared.v4.u32 [%1], {%2,%3,%4,%5};\n\t@p st.global.v4.u32 [%0], {%2,%3,%4,%5};\n\t}"
                                 ::"l"(o + (64 * (i & 1) + (i >> 1)) * DM), "r"((xa ^ (8 * (i & 2))) + 32768 * ph + 2048 * (i & 1) + 64 * (i & 2)),
                                   "r"(s[i][0]), "r"(s[i][1]), "r"(s[i][2]), "r"(s[i][3]), "r"(mk[i & 1] & (1u << (i >> 1))) : "memory");
            } else {
#pragma unroll
                for (int i = 0; i < 4; i++) sts128(so + ST2 * ph + 512 * (i & 1) + 64 * (i & 2), s[i][0], s[i][1], s[i][2], s[i][3]);
                fence_async();
                if (ph == FINE) STAMP(5);
                __syncwarp();
                if (elect_one()) {
                    asm volatile("cp.async.bulk.tensor.5d.global.shared::cta.bulk_group [%0, {%2, %5, %3, %5, %4}], [%1];"
                                 ::"l"(&maps.out), "r"(stg + ST2 * ph), "r"(16 * cl), "r"(2 * (w & 3)), "r"(4 * box), "r"(0) : "memory");
                }
            }
        };
        Tails tl;
        tl.start(sb + OFF_LC + 16 * lane, priv, lc.w, lane);
        send(IC<0>());
        tl.run<0, 4>(acc, priv, lc.w, lane);
        send(IC<1>());
        STAMP(8);
        tl.run<4, FIN_A>(acc, priv, lc.w, lane);
        if (FIN_A == FIN_B || w < 4) finish(0);
        tl.run<FIN_A, FIN_B>(acc, priv, lc.w, lane);
        if (FIN_A != FIN_B && FIN_B < 12 && w >= 4) finish(0);
        tl.run<FIN_B, 12>(acc, priv, lc.w, lane);
        send(IC<2>());
        STAMP(9);
        if (FIN_A != FIN_B && FIN_B == 12 && w >= 4) finish(0);
        tl.run<12, 20>(acc, priv, lc.w, lane);
        STAMP(11);
        send(IC<3>());
        finish(1);
        STAMP(12);
        __syncwarp();
        if (elect_one()) mbar_arrive(bar0 + 8 * B_ST);
        cluster_arrive();
        asm volatile("cp.async.bulk.commit_group;" ::: "memory");
        asm volatile("cp.async.bulk.wait_group.read 0;" ::: "memory");
        STAMP(13); GSTAMP(15);
    } else if (warp < 12) {
        const int a = warp - 8, at = 32 * a + lane, g = lane >> 2, t = lane & 3;
        STAMP(0);
        if (elect_one()) {
            const uint32_t cnt = a == 3 ? 0x48411122u : a == 2 ? 0x44444444u : 0x11111111u, tx = a == 0 ? 0x44444444u : a == 3 ? 0x00084444u : 0u;
#pragma unroll 1
            for (int i = 0; i < 8; i++) {
                mbar_init(bar0 + 64 * a + 8 * i, (cnt >> (4 * i)) & 15);
                const uint32_t n = (tx >> (4 * i)) & 15;
                if (n) mbar_expect_tx(bar0 + 64 * a + 8 * i, n << 11);
            }
            if (a < 3) mbar_init(bar0 + 8 * (B_KG + a), 8);
            asm volatile("fence.mbarrier_init.release.cluster;" ::: "memory");
            fence_async();
        }
        __syncwarp();
        cluster_arrive();
        if (FREG > 128) asm volatile("setmaxnreg.inc.sync.aligned.u32 %0;" ::"n"(FREG));
        const uint32_t epoch = ld_relaxed_32(p.scr + S_EPOCH);
        uint32_t* const pst = p.scr + S_STAT + 2048 * a + 16 * b + 2 * r + m;
        uint32_t* const pky = p.scr + S_KEY + 16 * b + at;
        if (lane < 16) st_relaxed_32(pst, 0u);
        if (at < 16) st_relaxed_32(pky, 0u);
        uint32_t* const py = p.scr + S_Y + 1024 * ((cl & ~3) + a) + 128 * (b & 7) + 32 * t + 4 * g;
        if (Y_RESET == 0) st_relaxed_128(py, 0u, 0u, 0u, 0u);
        const uint32_t gp = sb + OFF_GP;
        sts32(gp + 2048 + 4 * lane, ONES);
        lane_consts(sb + OFF_LC + 16 * at, a, lane);
        cluster_wait();
        STAMP(1);
        mbar_wait(bar0 + 8 * B_WR, 0);
        float ws[4] = {0.f, 0.f, 0.f, 0.f};
#pragma unroll 1
        for (int k = 0; k < 4; k++) {
            const uint4 q = lds128(gp + k * 512 + lane * 16);
            mma_bf16(ws, ONES, ONES, ONES, ONES, q.x, q.y);
            mma_bf16(ws, ONES, ONES, ONES, ONES, q.z, q.w);
        }
        float wsum = ws[0] + ws[1];
        wsum += __shfl_xor_sync(0xffffffffu, wsum, 1);
        wsum += __shfl_xor_sync(0xffffffffu, wsum, 2);
        const uint32_t hsel = (epoch & 1) * (GU_CTAS * 128), want = (epoch & 1) ? 0x00008000u : 0x80000000u;
        const uint32_t tbit = (epoch ^ m) << 31, ktag = ((epoch + 1u) | 0x8000u) & 0xffffu;
        if (a == 0) { sts64(sb + OFF_MISC + 32 + 8 * lane, 0u, 0u); sts32(sb + OFF_MISC, want); }
        __syncwarp();
        if (elect_one()) mbar_arrive(bar0 + 8 * B_TAG);
        if (b < GU_CTAS) st_relaxed_32(p.scr + S_H + (GU_CTAS * 128 - hsel) + b * 128 + at, 0u);
        {
            uint32_t ra[4], rb[4];
#pragma unroll
            for (int i = 0; i < 4; i++) {
                ra[i] = sb + OFF_ROWS + 2048 * a + 128 * (r + 8 * (m & 1)) + (((2 * i + (m >> 1)) ^ r) << 4);
                rb[i] = sb + OFF_ROWS + 2048 * a + 128 * (r + 8 * (m >> 1)) + (((2 * i + (m & 1)) ^ r) << 4);
            }
            uint32_t wa = r == 1 ? gp + 128 * a + 16 * m : gp + 2048;
            const uint32_t wstep = r == 1 ? 512 : 0;
            float cs[2][4] = {}, q1[2][4] = {}, q2[2][4] = {};
#pragma unroll 1
            for (int k = 0; k < 4; k++) {
                uint32_t x[4][4], z[4][4], wf[2][4];
                ldsm4(wf[0], wa); ldsm4(wf[1], wa + 64);
                mbar_wait(bar0 + 8 * (B_ROW + k), 0);
                STAMP(2);
#pragma unroll
                for (int i = 0; i < 4; i++) {
                    ldsm4(x[i], ra[i] + 8192 * k);
                    if (LN_DUP) ldsm4(z[i], rb[i] + 8192 * k);
                    else { z[i][0] = x[i][0]; z[i][1] = x[i][2]; z[i][2] = x[i][1]; z[i][3] = x[i][3]; }
                }
#pragma unroll
                for (int i = 0; i < 4; i++) {
                    mma_bf16(cs[i & 1], x[i][0], x[i][1], x[i][2], x[i][3], wf[i >> 1][2 * (i & 1)], wf[i >> 1][2 * (i & 1) + 1]);
                    mma_bf16(q1[i & 1], x[i][0], x[i][1], x[i][2], x[i][3], z[i][0], z[i][1]);
                    mma_bf16(q2[i & 1], x[i][0], x[i][1], x[i][2], x[i][3], z[i][2], z[i][3]);
                }
                wa += wstep;
            }
            const uint32_t pa = gp + 2304 + 256 * a;
#pragma unroll
            for (int i = 0; i < 4; i++) cs[0][i] += cs[1][i];
            if (t == 0) sts128f(pa + 16 * g, cs[0]);
            if (t == (g >> 1)) sts64(pa + 128 + 8 * g, __float_as_uint((g & 1) ? q1[0][1] + q1[1][1] : q1[0][0] + q1[1][0]),
                                     __float_as_uint((g & 1) ? q2[0][3] + q2[1][3] : q2[0][2] + q2[1][2]));
            named_sync(1, 128);
            uint2 u[4];
            float sq4[4];
#pragma unroll
            for (int i = 0; i < 4; i++) {
                u[i] = lds64(gp + 2304 + 256 * i + 16 * r + 8 * (m & 1));
                sq4[i] = lds32f(gp + 2304 + 128 + 256 * i + 8 * r + 4 * (m & 1));
            }
            const float mu = ((__uint_as_float(u[0].x) + __uint_as_float(u[1].x)) + (__uint_as_float(u[2].x) + __uint_as_float(u[3].x))) * (1.f / DM);
            const float sw = (__uint_as_float(u[0].y) + __uint_as_float(u[1].y)) + (__uint_as_float(u[2].y) + __uint_as_float(u[3].y));
            const float e2 = ((sq4[0] + sq4[1]) + (sq4[2] + sq4[3])) * (1.f / DM), var = fmaf(-mu, mu, e2);
            uint32_t ms = mean_std(mu, var);
            float sc = (sw - bf_round(mu) * wsum) * rcpf(bf_hi(ms));
            if (__any_sync(0xffffffffu, !(e2 <= 5.f * var))) {
                const uint2 c = ln_centred(sb, mu);
                ms = c.x; sc = __uint_as_float(c.y);
            }
            if (lane < 16) st_relaxed_32(pst, ms | tbit);
            if (at < 16) st_relaxed_32(pky, pack_bf16(0.f, sc) | ktag);
            if (lane < 8) mbar_arrive(bar0 + 8 * (B_EMPTY + lane));
        }
        __syncwarp();
        cluster_arrive();
        STAMP(3); GSTAMP(14);
        uint32_t mykey;
        {
            const uint32_t* sl = p.scr + S_SEL + 32 * (cl & 3) + 2 * g;
            uint2 q;
#pragma unroll 1
            do {
                __nanosleep(SEL_SLEEP);
                q = ld_relaxed_64(sl);
            } while (!__all_sync(0xffffffffu, q.y == ((epoch + 1u) | 0x8000u)));
            mykey = q.x;
        }
        STAMP(4);
        if (a == 0) {
            const uint32_t tok = ~mykey & 0xffffu;
            if (t == 0) asm volatile("red.shared.or.b32 [%0], %1;" ::"r"(sb + OFF_MISC + 32 + 4 * (tok >> 5)), "r"(1u << (tok & 31u)) : "memory");
            sts32(sb + OFF_MISC + 4, __reduce_or_sync(0xffffffffu, 1u << (4 * (tok >> 8) + ((tok >> 1) & 3))));
            __syncwarp();
            if (elect_one()) { mbar_arrive(bar0 + 8 * B_RECV); mbar_arrive(bar0 + 8 * (B_RECV + 1)); }
        }
        if (b < GU_CTAS) {
            const uint32_t tok = 0xffffu - (mykey & 0xffffu);
            {
                const uint32_t tk = __shfl_sync(0xffffffffu, tok, 16 * h + 4 * a);
                if (elect_one())
                    asm volatile("cp.async.bulk.shared::cluster.global.mbarrier::complete_tx::bytes.multicast::cluster [%0], [%1], 2048, [%2], %3;"
                                 ::"r"(sb + OFF_XS + (4 * h + a) * ROW_PITCH), "l"(p.u + (size_t)tk * DM), "r"(bar0 + 8 * B_XS), "h"((uint16_t)3) : "memory");
            }
            uint2 rec;
#pragma unroll 1
            do {
                rec = ld_relaxed_64(p.scr + S_STAT + 2048 * a + (tok & ~15u) + 2 * (tok & 7u));
            } while (!__all_sync(0xffffffffu, ((__byte_perm(rec.x, rec.y, 0x7632) ^ want) & 0x80008000u) == 0));
            const uint32_t mst = (tok & 8u) ? rec.y : rec.x;
            const uint32_t m2 = __byte_perm(mst, 0, 0x1010);
            const float rs = rcpf(__uint_as_float(mst & 0x7fff0000u));
            const float r0 = __shfl_sync(0xffffffffu, rs, 8 * t), r1 = __shfl_sync(0xffffffffu, rs, 8 * t + 4);
            float gacc[4][4];
#pragma unroll
            for (int i = 0; i < 4; i++) { gacc[i][0] = gacc[i][1] = gacc[i][2] = gacc[i][3] = 0.f; }
            const int k = r + 8 * (m >> 1);
            uint32_t wa[4];
#pragma unroll
            for (int mt = 0; mt < 4; mt++) wa[mt] = 1024 * a + (((m & 1) * 4096) ^ p.up_first) + k * 64 + ((((k >> 1) & 3) ^ mt) << 4);
            const uint32_t xa = sb + OFF_XS + r * ROW_PITCH + 32 * a + 16 * (m & 1) + 128 * (m >> 1);
#pragma unroll 1
            for (int c = 0; c < 4; c++) {
                uint32_t af[4][4][4], xb[2][4];
                const uint32_t half = sb + OFF_RING + 32768 * (c & 1), fb = bar0 + 8 * B_FULL + 32 * (c & 1);
#pragma unroll
                for (int j = 0; j < 4; j++) {
                    mbar_wait(fb + 8 * j, c >> 1);
                    if (j == 3) STAMP(12);
#pragma unroll
                    for (int mt = 0; mt < 4; mt++) ldsm4t(af[j][mt], wa[mt] + half + j * 8192);
                    __syncwarp();
                    if (elect_one()) mbar_arrive(fb + 8 * (B_EMPTY - B_FULL + j));
                    if (j == GU_SPLIT) {
                        mbar_wait(bar0 + 8 * B_XS, 0);
#pragma unroll
                        for (int i = 0; i < 2; i++) {
                            ldsm4(xb[i], xa + 512 * c + 256 * i);
#pragma unroll
                            for (int e = 0; e < 4; e++) xb[i][e] = as_u(__hsub2(as_b2(xb[i][e]), as_b2(m2)));
                        }
                    }
                    if (j == 3) STAMP(1);
                    if (j >= GU_SPLIT) {
#pragma unroll
                        for (int ks = j == GU_SPLIT ? 0 : j; ks <= j; ks++) {
#pragma unroll
                            for (int mt = 0; mt < 4; mt++)
                                mma_bf16v(gacc[mt], af[ks][mt], xb[ks >> 1][2 * (ks & 1)], xb[ks >> 1][2 * (ks & 1) + 1]);
                        }
                    }
                }
            }
            STAMP(6);
#pragma unroll
            for (int mt = 0; mt < 4; mt++) sts128f(gp + 2048 * a + mt * 512 + lane * 16, gacc[mt]);
            named_sync(1, 128);
            {
                uint4 q[4];
#pragma unroll
                for (int wq = 0; wq < 4; wq++) q[wq] = lds128(gp + 2048 * wq + 16 * at);
                const uint32_t g2 = pack_bf16(r0 * ((__uint_as_float(q[0].x) + __uint_as_float(q[1].x)) + (__uint_as_float(q[2].x) + __uint_as_float(q[3].x))),
                                              r1 * ((__uint_as_float(q[0].y) + __uint_as_float(q[1].y)) + (__uint_as_float(q[2].y) + __uint_as_float(q[3].y))));
                const uint32_t u2 = pack_bf16(r0 * ((__uint_as_float(q[0].z) + __uint_as_float(q[1].z)) + (__uint_as_float(q[2].z) + __uint_as_float(q[3].z))),
                                              r1 * ((__uint_as_float(q[0].w) + __uint_as_float(q[1].w)) + (__uint_as_float(q[2].w) + __uint_as_float(q[3].w))));
                const uint32_t s2 = pack_bf16(bf_lo(g2) * rcpf(1.f + ex2f(-L2E * bf_lo(g2))), bf_hi(g2) * rcpf(1.f + ex2f(-L2E * bf_hi(g2))));
                uint32_t hw;
                asm volatile("movmatrix.sync.aligned.m8n8.trans.b16 %0, %1;" : "=r"(hw) : "r"(as_u(__hmul2(as_b2(s2), as_b2(u2)))));
                if (hw == 0u) hw = 0x80008000u;
                st_relaxed_32(p.scr + S_H + hsel + b * 128 + at, hw);
            }
            STAMP(7);
        }
        const uint32_t ytag = 1u + (epoch & 1);
        {
            const uint32_t* hp = p.scr + S_H + hsel + (b & 7) * 1792 + 4 * at;
            const uint32_t wa = sb + OFF_RING + 128 * (r + 8 * (m >> 1)) + (((2 * a + (m & 1)) ^ r) << 4);
            uint32_t af[DN_RUN][4][4], hb[4];
            float dacc[4][4] = {};
            auto load_w = [&](int s) {
                mbar_wait(bar0 + 8 * (B_FULL + s), 0);
                if (s == 6) STAMP(13);
#pragma unroll
                for (int j = 0; j < 4; j++) ldsm4t(af[s % DN_RUN][j], wa + s * 8192 + j * 2048);
            };
            auto run = [&](int s) {
#pragma unroll
                for (int j = 0; j < 4; j++) {
                    if (!(j & 1)) ldsm4(hb, sb + OFF_XS + 16 * lane + 1024 * s + 256 * j);
                    mma_bf16v(dacc[j], af[s % DN_RUN][j], hb[2 * (j & 1)], hb[2 * (j & 1) + 1]);
                }
            };
            auto get_h = [&]() {
                uint4 hq[4];
#pragma unroll 1
                do {
                    __nanosleep(H_SLEEP);
#pragma unroll
                    for (int j = 0; j < 4; j++) hq[j] = ld_relaxed_128(hp + (j < 3 ? 512 * j : 1280));
                } while (!__all_sync(0xffffffffu, min(min(hq[0].w, hq[1].w), min(hq[2].w, hq[3].w)) != 0));
#pragma unroll
                for (int j = 0; j < 4; j++) sts128(sb + OFF_XS + 16 * at + (j < 3 ? 2048 * j : 5120), hq[j].x, hq[j].y, hq[j].z, hq[j].w);
            };
            if (b >= GU_CTAS) get_h();
            if (Y_RESET == 1) st_relaxed_128(py, 0u, 0u, 0u, 0u);
#pragma unroll
            for (int s = 0; s < DN_PRE; s++) load_w(s);
            if (b < GU_CTAS) get_h();
            STAMP(2);
#pragma unroll
            for (int s = DN_PRE; s < DN_RUN; s++) load_w(s);
            named_sync(1, 128);
            STAMP(8);
#pragma unroll
            for (int s = 0; s < DN_RUN; s++) run(s);
#pragma unroll
            for (int s = DN_RUN; s < 7 - DN_LAST; s++) load_w(s);
#pragma unroll
            for (int s = DN_RUN; s < 7 - DN_LAST; s++) run(s);
            if (DN_LAST) { load_w(6); run(6); }
            uint32_t y[4];
#pragma unroll
            for (int j = 0; j < 4; j++) y[j] = (__float_as_uint((dacc[0][j] + dacc[1][j]) + (dacc[2][j] + dacc[3][j])) & ~3u) | ytag;
            st_relaxed_128(py, y[0], y[1], y[2], y[3]);
        }
        STAMP(9);
        {
            const uint32_t key = __shfl_sync(0xffffffffu, mykey, 8 * a + 4 * (m >> 1));
            const uint32_t tok = 0xffffu - (key & 0xffffu);
            const float sg = bf_round(rcpf(1.f + ex2f(-L2E * bf_lo(unorder_key(key >> 16)))));
            const uint32_t xo = sb + OFF_X + 32 * (tok & ~63u) + 128 * (tok & 15u) + 2 * (tok & 48u) + ((2 * (lane & 15)) ^ ((tok & 1u) << 4));
            if (((tok >> 8) & 1) == h) {
                const uint32_t* yp = p.scr + S_Y + 1024 * cl + 32 * a + 4 * r + 2 * (m & 1) + (m >> 1);
                uint32_t pp[8], bad;
#pragma unroll 1
                do {
                    bad = 0;
#pragma unroll
                    for (int q = 0; q < 8; q++) pp[q] = ld_relaxed_32(yp + 128 * q);
#pragma unroll
                    for (int q = 0; q < 8; q++) bad |= pp[q] ^ ytag;
                } while (bad & 3u);
                const float y = ((__uint_as_float(pp[0]) + __uint_as_float(pp[1])) + (__uint_as_float(pp[2]) + __uint_as_float(pp[3]))) +
                                ((__uint_as_float(pp[4]) + __uint_as_float(pp[5])) + (__uint_as_float(pp[6]) + __uint_as_float(pp[7])));
                const uint32_t upd = pack_bf16(bf_round(y) * sg, 0.f);
                STAMP(11);
                mbar_wait(bar0 + 8 * B_ST, 0);
                uint32_t o;
                asm volatile("ld.shared.u16 %0, [%1];" : "=r"(o) : "r"(xo));
                asm volatile("st.global.u16 [%0], %1;" ::"l"(p.out + (size_t)tok * DM + 16 * cl + (lane & 15)), "r"(badd2(o, upd)) : "memory");
            }
            __syncwarp();
            if (elect_one()) mbar_arrive(bar0 + 8 * B_DONE);
        }
        STAMP(10); GSTAMP(15);
    } else {
        asm volatile("setmaxnreg.dec.sync.aligned.u32 %0;" ::"n"(FREG <= 136 ? 40 : 512 - 2 * NREG - FREG));
        const int q = warp - 12;
        sts32(sb + OFF_MISC + 16 + 4 * q, clk());
        const uint32_t t0 = __shfl_sync(0xffffffffu, lds32v(sb + OFF_MISC + 16 + 4 * q), 0);
        STAMP(0);
        if (q == 1) GSTAMP(14);
        const bool one = elect_one();
        const uint32_t rbar = bar0 + 8 * (B_ROW + q);
        if (one) {
            asm volatile("prefetch.tensormap [%0];" ::"l"(&maps.rows) : "memory");
            mbar_init(rbar, 1);
            if (q == 3) mbar_init(bar0 + 8 * B_WR, 1);
            fence_async();
            mbar_expect_tx(rbar, 8192);
            if (q == 3) {
                mbar_expect_tx(bar0 + 8 * B_WR, 2048);
                bulk_g2s(sb + OFF_GP, p.wr, 2048, bar0 + 8 * B_WR);
            }
        }
        __syncwarp();
        cluster_arrive();
        wait_until(t0 + ROW_DELAY + q * ROW_PERIOD);
        if (one) {
            tma_load_3d(sb + OFF_ROWS + 8192 * q, &maps.rows, 16 * b, 4 * q, rbar);
            asm volatile("prefetch.tensormap [%0];" ::"l"(&maps.u + q) : "memory");
        }
        __syncwarp();
        cluster_wait();
        cluster_arrive();
        STAMP(1);
        wait_until(t0 + X_DELAY + q * X_PERIOD);
        if (one) tma_load_4d_both(sb + OFF_X + 8192 * (4 * h + q), &maps.u, 16 * cl, 4 * (4 * h + q), bar0 + 8 * (B_X + 4 * h + q));
        STAMP(2);
        const char* src = (const char*)((b >> 6) ? p.wu : p.wg) + (64 * q + (b & 63)) * 7168 + 128 * lane;
        const uint32_t phase = t0 + PF_START + (b * PF_PERIOD >> 7) + q * PF_PERIOD;
        auto fill = [&](int j, uint32_t due, const CUtensorMap* map, int c0, int c3) {
            const uint32_t bar = bar0 + 8 * (B_FULL + q + 4 * (j & 1));
            wait_until(due);
            mbar_wait(bar + 8 * (B_EMPTY - B_FULL), (j >> 1) & 1);
            if (one) {
                mbar_expect_tx(bar, 8192);
                tma_load_4d(sb + OFF_RING + (q + 4 * (j & 1)) * 8192, map, c0, c3, bar);
            }
            STAMP(3 + (j >> 1));
        };
#pragma unroll 1
        for (int j = 0; j < 4; j++) {
            wait_until(phase + 4 * j * PF_PERIOD);
            asm volatile("prefetch.global.L2 [%0];" ::"l"(src) : "memory");
            if (lane < 24) asm volatile("prefetch.global.L2 [%0];" ::"l"(src + 4096) : "memory");
            src += 256 * 7168;
            STAMP(6);
            if (b < GU_CTAS) fill(j, t0 + LD_START + (b * PHG >> 7) + (q + 4 * j) * LD_PERIOD, &maps.wgu, 32 * b, q + 4 * j);
        }
#pragma unroll 1
        for (int j = 4; j < (q < 3 ? 6 : 5); j++)
            fill(j, phase + 4 * j * PF_PERIOD + (q + 4 * j - 16) * WD_EXTRA, &maps.wd, 64 * (b >> 3), 7 * (b & 7) + q + 4 * j - 16);
        if (q >= 2) mbar_wait_bounded(bar0 + 8 * (B_DONE - 2 + q), 0);
    }
    cluster_wait();
}

typedef CUresult (*EncodeFn)(CUtensorMap*, CUtensorMapDataType, cuuint32_t, void*, const cuuint64_t*, const cuuint64_t*,
                             const cuuint32_t*, const cuuint32_t*, CUtensorMapInterleave, CUtensorMapSwizzle,
                             CUtensorMapL2promotion, CUtensorMapFloatOOBfill);

void make_map(EncodeFn enc, CUtensorMap* m, int rank, const void* ptr, const cuuint64_t (&dims)[5], const cuuint64_t (&str)[4],
              const cuuint32_t (&box)[5], CUtensorMapSwizzle sw, CUtensorMapL2promotion pr) {
    const cuuint32_t es[5] = {1, 1, 1, 1, 1};
    CUresult rc = enc(m, CU_TENSOR_MAP_DATA_TYPE_BFLOAT16, rank, const_cast<void*>(ptr), dims, str, box, es, CU_TENSOR_MAP_INTERLEAVE_NONE, sw, pr,
                      CU_TENSOR_MAP_FLOAT_OOB_FILL_NONE);
    (void)rc;
}

}

extern "C" void kernel_launch(void* const* d_in, const int* in_sizes, int n_in, void* d_out, int out_size) {
    (void)in_sizes; (void)n_in; (void)out_size;
    static EncodeFn enc = nullptr;
    static void* scr = nullptr;
    if (!enc) {
        void* fn = nullptr;
        cudaDriverEntryPointQueryResult q;
        cudaGetDriverEntryPoint("cuTensorMapEncodeTiled", &fn, cudaEnableDefault, &q);
        enc = (EncodeFn)fn;
        cudaGetSymbolAddress(&scr, g_scr);
        cudaFuncSetAttribute(fused_kernel, cudaFuncAttributeMaxDynamicSharedMemorySize, SMEM_BYTES);
    }
    Maps maps;
    const uintptr_t ag = (uintptr_t)d_in[9], au = (uintptr_t)d_in[10];
    const auto noprom = CU_TENSOR_MAP_L2_PROMOTION_NONE, prom = CU_TENSOR_MAP_L2_PROMOTION_L2_128B;
    make_map(enc, &maps.rows, 3, d_in[0], {64, SEQ, 16, 1}, {2048, 128, 0}, {64, 16, 4, 1}, CU_TENSOR_MAP_SWIZZLE_128B, noprom);
    make_map(enc, &maps.u, 4, d_in[0], {DM, 4, 16, 32}, {32768, 2048, 131072}, {16, 4, 16, 4}, CU_TENSOR_MAP_SWIZZLE_32B, noprom);
    make_map(enc, &maps.out, 5, d_out, {DM, 4, 8, 2, 32}, {32768, 2048, 16384, 131072}, {16, 4, 2, 2, 4}, CU_TENSOR_MAP_SWIZZLE_NONE, noprom);
    make_map(enc, &maps.wgu, 4, (const void*)(ag < au ? ag : au), {FF, 64, 2, 16}, {FF * 2, ag < au ? au - ag : ag - au, 64 * FF * 2}, {32, 64, 2, 1},
             CU_TENSOR_MAP_SWIZZLE_64B, prom);
    make_map(enc, &maps.wd, 4, d_in[11], {DM, 64, 1, 56}, {2048, 131072, 131072}, {64, 64, 1, 1}, CU_TENSOR_MAP_SWIZZLE_128B, prom);
    Ptrs p;
    p.u = (const __nv_bfloat16*)d_in[0];
    p.logA = (const __nv_bfloat16*)d_in[1];
    p.Aim = (const __nv_bfloat16*)d_in[2];
    p.Cre = (const __nv_bfloat16*)d_in[3];
    p.Cim = (const __nv_bfloat16*)d_in[4];
    p.ldt = (const __nv_bfloat16*)d_in[5];
    p.dsk = (const __nv_bfloat16*)d_in[6];
    p.wr = (const __nv_bfloat16*)d_in[8];
    p.wg = (const __nv_bfloat16*)d_in[9];
    p.wu = (const __nv_bfloat16*)d_in[10];
    p.out = (__nv_bfloat16*)d_out;
    p.scr = (uint32_t*)scr;
    p.up_first = ag < au ? 0 : 4096;
    p.zero = 0;
    fused_kernel<<<NCTA + 2, NTHR, SMEM_BYTES, cudaStreamPerThread>>>(p, maps);
}
```

```cpp
#include <cuda_runtime.h>
#include <cuda_bf16.h>
#include <cuda_fp16.h>
#include <cuda.h>
#include <stdint.h>

namespace {

constexpr int SEQ = 2048, DM = 1024, NMODE = 128, FF = 3584;
constexpr int NCTA = 128, NTHR = 512;
constexpr int GU_CTAS = 112;

constexpr int OFF_X = 0;
constexpr int OFF_RING = 65536;
constexpr int ROW_PITCH = 2064;
constexpr int OFF_ROWS = OFF_RING + 32768;
constexpr int OFF_XS = OFF_RING + 65536;
constexpr int OFF_PRIV = OFF_XS + 8 * ROW_PITCH;
constexpr int PRIV = 8768;
constexpr int PLANE = 2240;
constexpr int OFF_GP = OFF_PRIV + 8 * PRIV;
constexpr int OFF_LC = OFF_GP + 8192;
constexpr int OFF_BAR = OFF_LC + 2048;
constexpr int OFF_MISC = OFF_BAR + 352;
constexpr int OFF_STAMP = OFF_MISC + 288;
constexpr int SMEM_BYTES = OFF_STAMP;

constexpr int B_X = 0, B_FULL = 8, B_EMPTY = 16, B_RECV = 24, B_XS = 28, B_DONE = 29, B_ST = 30, B_ROW = 32, B_WR = 36, B_KG = 37, B_VT = 38, B_PV = 39;

constexpr int T_DENSE = 4416;
constexpr int T_PATCH = T_DENSE + 2176;
constexpr int T_S4 = T_PATCH + 112;
constexpr int T_S8 = T_S4 + 736;
constexpr int REC = 272;

#define KG_UNROLL 2
constexpr int KGU = KG_UNROLL;
constexpr uint32_t SPIN_LIMIT = 1u << 22;
#define ROW_DELAY 300
#define H_SLEEP 0
#define NPRE 4
#define SEL_SLEEP 40
#define ROW_PERIOD 560
#define X_PERIOD 60
#define FINE 2
#define INC_AT 1
#define NREG 168
#define DN_RUN 6
#define FREG 144
#define NACC 1
#define LAST_DIRECT 0
#define DN_PRE 5
#define DN_LAST 1
#define GU_SPLIT 2
#define FIN_A 4
#define FIN_B 12
#define TORD 0
#define CW_EARLY 0
#define WAKE 63
#define LN_DUP 0
#define PHG 480
#define STAT_SLEEP 0
#define ST_GATE 3
#define X_DELAY 2600
#define PF_START 3400
#define PF_PERIOD 539
#define WD_EXTRA (PF_PERIOD / 7)
#define LD_LAG 300
#define LD_START 5300
#define LD_PERIOD ((PF_START + 16 * PF_PERIOD + LD_LAG - LD_START) / 15)

constexpr int S_STAT = 0;
constexpr int S_KEY = S_STAT + 8192;
constexpr int S_SEL = S_KEY + 2048;
constexpr int S_EPOCH = S_SEL + 128;
constexpr int S_H = S_EPOCH + 32;
constexpr int S_Y = S_H + 2 * GU_CTAS * 128;
constexpr int S_END = S_Y + 64 * 1024;
__device__ __align__(1024) uint32_t g_scr[S_END];

struct Ptrs {
    const __nv_bfloat16 *logA, *Aim, *Cre, *Cim, *ldt, *dsk, *u, *wr;
    uint32_t* scr;
    const __nv_bfloat16 *wg, *wu;
    __nv_bfloat16* out;
    uint32_t up_first;
    uint32_t zero;
};
struct Maps {
    CUtensorMap rows, u, out, wgu, wd;
};

__device__ __forceinline__ uint32_t clk() { uint32_t c; asm volatile("mov.u32 %0, %%clock;" : "=r"(c)); return c; }
#define STAMP(i) do { } while (0)
#define GSTAMP(i) do { } while (0)

template <int N> struct IC { static constexpr int value = N; };

__device__ __forceinline__ uint32_t s_u32(const void* p) { return (uint32_t)__cvta_generic_to_shared(p); }
__device__ __forceinline__ void mbar_init(uint32_t b, uint32_t n) {
    asm volatile("mbarrier.init.shared::cta.b64 [%0], %1;" ::"r"(b), "r"(n) : "memory");
}
__device__ __forceinline__ void mbar_expect_tx(uint32_t b, uint32_t bytes) {
    asm volatile("mbarrier.arrive.expect_tx.shared::cta.b64 _, [%0], %1;" ::"r"(b), "r"(bytes) : "memory");
}
__device__ __forceinline__ void mbar_arrive(uint32_t b) {
    asm volatile("mbarrier.arrive.shared::cta.b64 _, [%0];" ::"r"(b) : "memory");
}
__device__ __forceinline__ void mbar_arrive_peer(uint32_t b_cluster) {
    asm volatile("mbarrier.arrive.relaxed.cluster.shared::cluster.b64 _, [%0];" ::"r"(b_cluster) : "memory");
}
__device__ __forceinline__ void mbar_wait(uint32_t b, uint32_t parity) {
    asm volatile("{\n\t.reg .pred p;\nW:\n\tmbarrier.try_wait.parity.shared::cta.b64 p, [%0], %1;\n\t@!p bra W;\n\t}" ::"r"(b), "r"(parity) : "memory");
}
__device__ __forceinline__ void mbar_wait_bounded(uint32_t b, uint32_t parity) {
    asm volatile("{\n\t.reg .pred p;\n\t.reg .u32 c;\n\tmov.u32 c, 0;\n"
                 "W:\n\tmbarrier.try_wait.parity.shared::cta.b64 p, [%0], %1, 4000;\n\t@p bra D;\n\t"
                 "add.u32 c, c, 1;\n\tsetp.lt.u32 p, c, 1048576;\n\t@p bra W;\n\ttrap;\nD:\n\t}"
                 ::"r"(b), "r"(parity) : "memory");
}
__device__ __forceinline__ bool elect_one() {
    uint32_t p;
    asm volatile("{ .reg .pred P; elect.sync _|P, 0xffffffff; selp.u32 %0, 1, 0, P; }" : "=r"(p));
    return p != 0;
}
__device__ __forceinline__ uint32_t mapa(uint32_t a, uint32_t rank) {
    uint32_t r;
    asm("mapa.shared::cluster.u32 %0, %1, %2;" : "=r"(r) : "r"(a), "r"(rank));
    return r;
}
__device__ __forceinline__ void cluster_arrive() { asm volatile("barrier.cluster.arrive.relaxed.aligned;" ::: "memory"); }
__device__ __forceinline__ void cluster_wait() { asm volatile("barrier.cluster.wait.aligned;" ::: "memory"); }
__device__ __forceinline__ void tma_load_3d(uint32_t dst, const CUtensorMap* m, int c1, int c2, uint32_t bar) {
    asm volatile("cp.async.bulk.tensor.3d.shared::cluster.global.mbarrier::complete_tx::bytes [%0], [%1, {%3, %4, %5}], [%2];"
                 ::"r"(dst), "l"(m), "r"(bar), "r"(0), "r"(c1), "r"(c2) : "memory");
}
__device__ __forceinline__ void tma_load_4d(uint32_t dst, const CUtensorMap* m, int c0, int c3, uint32_t bar) {
    uint64_t pol;
    asm("createpolicy.fractional.L2::evict_first.b64 %0, 1.0;" : "=l"(pol));
    asm volatile("cp.async.bulk.tensor.4d.shared::cluster.global.mbarrier::complete_tx::bytes.L2::cache_hint [%0], [%1, {%3, %5, %5, %4}], [%2], %6;"
                 ::"r"(dst), "l"(m), "r"(bar), "r"(c0), "r"(c3), "r"(0), "l"(pol) : "memory");
}
__device__ __forceinline__ void wait_until(uint32_t t) {
    asm volatile("{\n\t.reg .pred p;\n\t.reg .s32 c;\nW:\n\tmov.u32 c, %%clock;\n\tsub.s32 c, %0, c;\n\tshr.s32 c, c, 2;\n\tsetp.gt.s32 p, c, %1;\n\t"
                 "@p nanosleep.u32 c;\n\t@p bra.uni W;\n\t}" ::"r"(t), "n"(WAKE) : "memory");
}
__device__ __forceinline__ void tma_load_4d_both(uint32_t dst, const CUtensorMap* m, int c0, int c3, uint32_t bar) {
    asm volatile("cp.async.bulk.tensor.4d.shared::cluster.global.mbarrier::complete_tx::bytes.multicast::cluster [%0], [%1, {%3, %6, %6, %4}], [%2], %5;"
                 ::"r"(dst), "l"(m), "r"(bar), "r"(c0), "r"(c3), "h"((uint16_t)3), "r"(0) : "memory");
}
__device__ __forceinline__ void bulk_g2s(uint32_t dst, const void* src, uint32_t bytes, uint32_t bar) {
    asm volatile("cp.async.bulk.shared::cluster.global.mbarrier::complete_tx::bytes [%0], [%1], %2, [%3];"
                 ::"r"(dst), "l"(src), "r"(bytes), "r"(bar) : "memory");
}
__device__ __forceinline__ void fence_async() { asm volatile("fence.proxy.async.shared::cta;" ::: "memory"); }
__device__ __forceinline__ void named_sync(int id, int n) { asm volatile("bar.sync %0, %1;" ::"r"(id), "r"(n) : "memory"); }

__device__ __forceinline__ void ldsm4(uint32_t* r, uint32_t a) {
    asm volatile("ldmatrix.sync.aligned.m8n8.x4.shared.b16 {%0,%1,%2,%3}, [%4];"
                 : "=r"(r[0]), "=r"(r[1]), "=r"(r[2]), "=r"(r[3]) : "r"(a));
}
__device__ __forceinline__ void ldsm4t(uint32_t* r, uint32_t a) {
    asm volatile("ldmatrix.sync.aligned.m8n8.x4.trans.shared.b16 {%0,%1,%2,%3}, [%4];"
                 : "=r"(r[0]), "=r"(r[1]), "=r"(r[2]), "=r"(r[3]) : "r"(a));
}
__device__ __forceinline__ void stsm4t(uint32_t a, const uint32_t* r) {
    asm volatile("stmatrix.sync.aligned.m8n8.x4.trans.shared.b16 [%0], {%1,%2,%3,%4};"
                 ::"r"(a), "r"(r[0]), "r"(r[1]), "r"(r[2]), "r"(r[3]) : "memory");
}
__device__ __forceinline__ uint32_t lds32(uint32_t a) { uint32_t v; asm volatile("ld.shared.u32 %0, [%1];" : "=r"(v) : "r"(a)); return v; }
__device__ __forceinline__ uint32_t lds32v(uint32_t a) { uint32_t v; asm volatile("ld.volatile.shared.u32 %0, [%1];" : "=r"(v) : "r"(a)); return v; }
__device__ __forceinline__ uint2 lds64(uint32_t a) { uint2 v; asm volatile("ld.shared.v2.u32 {%0,%1}, [%2];" : "=r"(v.x), "=r"(v.y) : "r"(a)); return v; }
__device__ __forceinline__ uint4 lds128(uint32_t a) {
    uint4 v; asm volatile("ld.shared.v4.u32 {%0,%1,%2,%3}, [%4];" : "=r"(v.x), "=r"(v.y), "=r"(v.z), "=r"(v.w) : "r"(a)); return v;
}
template <int D> __device__ __forceinline__ void sts16x2(uint32_t a, float x) {
    asm volatile("{ .reg .b16 h; cvt.rn.bf16.f32 h, %1; st.shared.b16 [%0], h; st.shared.b16 [%0 + %2], h; }" ::"r"(a), "f"(x), "n"(D) : "memory");
}
__device__ __forceinline__ void sts32(uint32_t a, uint32_t v) { asm volatile("st.shared.u32 [%0], %1;" ::"r"(a), "r"(v) : "memory"); }
__device__ __forceinline__ void sts64(uint32_t a, uint32_t x, uint32_t y) { asm volatile("st.shared.v2.u32 [%0], {%1,%2};" ::"r"(a), "r"(x), "r"(y) : "memory"); }
__device__ __forceinline__ void sts128(uint32_t a, uint32_t x, uint32_t y, uint32_t z, uint32_t w) {
    asm volatile("st.shared.v4.u32 [%0], {%1,%2,%3,%4};" ::"r"(a), "r"(x), "r"(y), "r"(z), "r"(w) : "memory");
}
__device__ __forceinline__ void sts128f(uint32_t a, const float* c) {
    asm volatile("st.shared.v4.f32 [%0], {%1,%2,%3,%4};" ::"r"(a), "f"(c[0]), "f"(c[1]), "f"(c[2]), "f"(c[3]) : "memory");
}
__device__ __forceinline__ uint2 ldg64(const void* p) {
    uint2 v; asm volatile("ld.global.nc.L1::no_allocate.v2.u32 {%0,%1}, [%2];" : "=r"(v.x), "=r"(v.y) : "l"(p)); return v;
}
__device__ __forceinline__ uint32_t ldg16(const void* p) {
    uint16_t v; asm volatile("ld.global.nc.u16 %0, [%1];" : "=h"(v) : "l"(p)); return v;
}
__device__ __forceinline__ uint32_t ld_relaxed_32(const void* p) {
    uint32_t v; asm volatile("ld.relaxed.gpu.global.u32 %0, [%1];" : "=r"(v) : "l"(p) : "memory"); return v;
}
__device__ __forceinline__ uint2 ld_relaxed_64(const void* p) {
    unsigned long long v;
    asm volatile("ld.relaxed.gpu.global.u64 %0, [%1];" : "=l"(v) : "l"(p) : "memory");
    return make_uint2((uint32_t)v, (uint32_t)(v >> 32));
}
__device__ __forceinline__ uint4 ld_relaxed_128(const void* p) {
    uint4 v; asm volatile("ld.relaxed.gpu.global.v4.u32 {%0,%1,%2,%3}, [%4];" : "=r"(v.x), "=r"(v.y), "=r"(v.z), "=r"(v.w) : "l"(p) : "memory"); return v;
}
__device__ __forceinline__ void st_relaxed_32(void* p, uint32_t v) {
    asm volatile("st.relaxed.gpu.global.u32 [%0], %1;" ::"l"(p), "r"(v) : "memory");
}
__device__ __forceinline__ void st_relaxed_128(void* p, uint32_t x, uint32_t y, uint32_t z, uint32_t w) {
    asm volatile("st.relaxed.gpu.global.v4.u32 [%0], {%1,%2,%3,%4};" ::"l"(p), "r"(x), "r"(y), "r"(z), "r"(w) : "memory");
}
__device__ __forceinline__ void st_relaxed_64(void* p, uint32_t x, uint32_t y) {
    asm volatile("st.relaxed.gpu.global.u64 [%0], %1;" ::"l"(p), "l"((unsigned long long)x | ((unsigned long long)y << 32)) : "memory");
}
__device__ __forceinline__ void mma_bf16(float* c, uint32_t a0, uint32_t a1, uint32_t a2, uint32_t a3, uint32_t b0, uint32_t b1) {
    asm("mma.sync.aligned.m16n8k16.row.col.f32.bf16.bf16.f32 {%0,%1,%2,%3}, {%4,%5,%6,%7}, {%8,%9}, {%0,%1,%2,%3};"
                 : "+f"(c[0]), "+f"(c[1]), "+f"(c[2]), "+f"(c[3]) : "r"(a0), "r"(a1), "r"(a2), "r"(a3), "r"(b0), "r"(b1));
}
__device__ __forceinline__ void mma_bf16v(float* c, const uint32_t* a, uint32_t b0, uint32_t b1) {
    asm volatile("mma.sync.aligned.m16n8k16.row.col.f32.bf16.bf16.f32 {%0,%1,%2,%3}, {%4,%5,%6,%7}, {%8,%9}, {%0,%1,%2,%3};"
                 : "+f"(c[0]), "+f"(c[1]), "+f"(c[2]), "+f"(c[3]) : "r"(a[0]), "r"(a[1]), "r"(a[2]), "r"(a[3]), "r"(b0), "r"(b1));
}
__device__ __forceinline__ void mma_bf16_z(float* c, uint32_t a0, uint32_t a1, uint32_t a2, uint32_t a3, uint32_t b0, uint32_t b1) {
    asm("mma.sync.aligned.m16n8k16.row.col.f32.bf16.bf16.f32 {%0,%1,%2,%3}, {%4,%5,%6,%7}, {%8,%9}, {%10,%10,%10,%10};"
        : "=f"(c[0]), "=f"(c[1]), "=f"(c[2]), "=f"(c[3]) : "r"(a0), "r"(a1), "r"(a2), "r"(a3), "r"(b0), "r"(b1), "f"(0.f));
}
__device__ __forceinline__ void mma_f16(float* c, const uint4& a, uint32_t b0, uint32_t b1) {
    asm("mma.sync.aligned.m16n8k16.row.col.f32.f16.f16.f32 {%0,%1,%2,%3}, {%4,%5,%6,%7}, {%8,%9}, {%0,%1,%2,%3};"
                 : "+f"(c[0]), "+f"(c[1]), "+f"(c[2]), "+f"(c[3]) : "r"(a.x), "r"(a.y), "r"(a.z), "r"(a.w), "r"(b0), "r"(b1));
}
__device__ __forceinline__ uint32_t pack_bf16(float lo, float hi) {
    uint32_t r; asm("cvt.rn.bf16x2.f32 %0, %1, %2;" : "=r"(r) : "f"(hi), "f"(lo)); return r;
}
__device__ __forceinline__ uint32_t pack_bf16v(float lo, float hi) {
    uint32_t r; asm("cvt.rn.satfinite.bf16x2.f32 %0, %1, %2;" : "=r"(r) : "f"(hi), "f"(lo)); return r;
}
__device__ __forceinline__ uint32_t pack_f16(float lo, float hi) {
    uint32_t r; asm("cvt.rn.f16x2.f32 %0, %1, %2;" : "=r"(r) : "f"(hi), "f"(lo)); return r;
}
__device__ __forceinline__ float bf_lo(uint32_t v) { return __uint_as_float(v << 16); }
__device__ __forceinline__ float bf_hi(uint32_t v) { return __uint_as_float(v & 0xffff0000u); }
__device__ __forceinline__ float bf_round(float x) { return __uint_as_float(pack_bf16(0.f, x)); }
__device__ __forceinline__ __nv_bfloat162 as_b2(uint32_t x) { return *reinterpret_cast<__nv_bfloat162*>(&x); }
__device__ __forceinline__ uint32_t as_u(__nv_bfloat162 x) { return *reinterpret_cast<uint32_t*>(&x); }
__device__ __forceinline__ uint32_t badd2(uint32_t a, uint32_t b) { uint32_t r; asm("add.rn.bf16x2 %0, %1, %2;" : "=r"(r) : "r"(a), "r"(b)); return r; }
__device__ __forceinline__ float rcpf(float x) { float r; asm("rcp.approx.ftz.f32 %0, %1;" : "=f"(r) : "f"(x)); return r; }
__device__ __forceinline__ float sqrtaf(float x) { float r; asm("sqrt.approx.ftz.f32 %0, %1;" : "=f"(r) : "f"(x)); return r; }
__device__ __forceinline__ float ex2f(float x) { float r; asm("ex2.approx.ftz.f32 %0, %1;" : "=f"(r) : "f"(x)); return r; }
constexpr float L2E = 1.4426950408889634f;
constexpr uint32_t ONES = 0x3f803f80u;

__device__ __forceinline__ uint2 recip2(uint32_t s2) {
    const uint32_t hi = pack_bf16(rcpf(bf_lo(s2)), rcpf(bf_hi(s2)));
    return make_uint2(hi, as_u(__hmul2(__hfma2(__hneg2(as_b2(s2)), as_b2(hi), as_b2(ONES)), as_b2(hi))));
}
__device__ __forceinline__ uint32_t normalize2(uint32_t x, __nv_bfloat162 m, __nv_bfloat162 rh, __nv_bfloat162 rl) {
    const __nv_bfloat162 d = __hsub2(as_b2(x), m);
    return as_u(__hfma2(d, rh, __hmul2(d, rl)));
}

__device__ __forceinline__ uint32_t unorder_key(uint32_t k16) { return k16 ^ ((k16 & 0x8000u) ? 0x8000u : 0xffffu); }

struct cplx { float r, i; };
__device__ __forceinline__ cplx csq(cplx a) { return {a.r * a.r - a.i * a.i, (a.r + a.r) * a.i}; }
__device__ __forceinline__ cplx csq_conj(cplx a) { return {a.r * a.r - a.i * a.i, (-a.r - a.r) * a.i}; }
__device__ __forceinline__ cplx cexpp(float a2, float th) {
    float m = ex2f(a2), s, c;
    __sincosf(th, &s, &c);
    return {m * c, m * s};
}
struct hc { __half2 r, i; };
__device__ __forceinline__ __half2 as_h2(uint32_t x) { return *reinterpret_cast<__half2*>(&x); }
__device__ __forceinline__ uint32_t as_u(__half2 x) { return *reinterpret_cast<uint32_t*>(&x); }
__device__ __forceinline__ hc hmul(hc a, hc b) {
    return {__hfma2(a.r, b.r, __hneg2(__hmul2(a.i, b.i))), __hfma2(a.r, b.i, __hmul2(a.i, b.r))};
}
__device__ __forceinline__ hc hpack(cplx a, cplx b) { return {as_h2(pack_f16(a.r, b.r)), as_h2(pack_f16(a.i, b.i))}; }
__device__ __forceinline__ void st_pair(uint32_t a, hc x, hc y) { sts128(a, as_u(x.r), as_u(x.i), as_u(y.r), as_u(y.i)); }
__device__ __forceinline__ void st_quad(uint32_t a, hc x, hc y) { sts128(a, as_u(x.r), as_u(y.r), as_u(x.i), as_u(y.i)); }

#define KSTAMP(i, dep) do { } while (0)
__device__ __forceinline__ void kgen_mma(float (&acc)[5][4], uint32_t priv, int lane, uint2 la, uint2 aim, uint2 cre, uint2 cim, float dt, uint32_t cs2) {
    const int g = lane >> 2, t = lane & 3;
#pragma unroll
    for (int i = 0; i < 5; i++) { acc[i][0] = acc[i][1] = acc[i][2] = acc[i][3] = 0.f; }
    const uint32_t wr = priv + lane * REC, rd = priv + 2 * t * REC;
    const float ndl = -dt * L2E;
#pragma unroll 1
    for (int ps = 0; ps < 2; ps++) {
        const uint32_t lw = ps ? la.y : la.x, iw = ps ? aim.y : aim.x;
        const uint32_t crw = as_u(__hmul2(as_b2(ps ? cre.y : cre.x), as_b2(cs2))), ciw = as_u(__hmul2(as_b2(ps ? cim.y : cim.x), as_b2(cs2)));
        const uint32_t ap = pack_bf16(ex2f(bf_lo(lw) * L2E), ex2f(bf_hi(lw) * L2E));
        const float a2[2] = {bf_lo(ap) * ndl, bf_hi(ap) * ndl}, th[2] = {bf_lo(iw) * dt, bf_hi(iw) * dt};
        cplx p1[2], p2[2], p4[2], p8[2], p32[2], p64[2], p128[2], p256[2], p512[2];
#pragma unroll
        for (int i = 0; i < 2; i++) {
            p1[i] = cexpp(a2[i], th[i]); p32[i] = cexpp(a2[i] * 32.f, th[i] * -32.f);
            p2[i] = csq(p1[i]); p4[i] = csq(p2[i]); p8[i] = csq_conj(p4[i]);
            p64[i] = csq(p32[i]); p128[i] = csq_conj(p64[i]); p256[i] = csq(p128[i]); p512[i] = csq(p256[i]);
        }
        const hc C = {as_h2(pack_f16(bf_lo(crw), bf_hi(crw))), as_h2(pack_f16(bf_lo(ciw), bf_hi(ciw)))};
        const hc z1 = hpack(p1[0], p1[1]), z2 = hpack(p2[0], p2[1]), z4 = hpack(p4[0], p4[1]);
        const hc y8 = hpack(p8[0], p8[1]), y32 = hpack(p32[0], p32[1]), y64 = hpack(p64[0], p64[1]);
        const hc z128 = hpack(p128[0], p128[1]), z256 = hpack(p256[0], p256[1]), z512 = hpack(p512[0], p512[1]);
        KSTAMP(8 + 3 * ps, z512.r);
        __syncwarp();
        const hc c1 = hmul(C, z1), c2 = hmul(C, z2), c5 = hmul(c1, z4), c6 = hmul(c2, z4);
        st_pair(wr + 160, hmul(c1, z128), hmul(c2, z128));
        st_pair(wr + 128, c1, c2);
        st_pair(wr + 176, hmul(c5, z128), hmul(c6, z128));
        st_pair(wr + 144, c5, c6);
        const hc y16 = hmul(y8, y8), y48 = hmul(y16, y32), y24 = hmul(y16, y8), y40 = hmul(y32, y8), y56 = hmul(y48, y8), y72 = hmul(y64, y8);
        st_quad(wr, {as_h2(0x3c003c00u), as_h2(0u)}, y8);
        st_quad(wr + 80, hmul(y64, y16), hmul(y64, y24));
        st_quad(wr + 16, y16, y24);
        st_quad(wr + 96, hmul(y64, y32), hmul(y64, y40));
        st_quad(wr + 32, y32, y40);
        st_quad(wr + 112, hmul(y64, y48), hmul(y64, y56));
        st_quad(wr + 48, y48, y56);
        st_quad(wr + 64, y64, y72);
        const hc z258 = hmul(z256, z2);
        st_pair(wr + 192, hmul(z256, z1), z258);
        st_pair(wr + 224, z2, hmul(z512, z4));
        st_pair(wr + 240, z2, hmul(z512, z512));
        st_pair(wr + 208, z258, z512);
        KSTAMP(9 + 3 * ps, z512.r);
        __syncwarp();
#pragma unroll KGU
        for (int k2 = 0; k2 < 4; k2++) {
#pragma unroll
            for (int s = 0; s < 2; s++) {
                const uint32_t o = rd + k2 * 8 * REC + s * REC;
                const uint4 A = lds128(o + 16 * g);
                const uint2 h = lds64(o + 128 + 8 * g);
                const uint4 M = lds128(o + 192 + 16 * (g & 1)), N = lds128(o + 224 + 8 * (g & 2));
                const hc H0 = {as_h2(h.x), as_h2(h.y)};
                const hc H1 = hmul(H0, {as_h2(N.x), as_h2(N.y)}), H2 = hmul(H0, {as_h2(M.x), as_h2(M.y)});
                const hc H3 = hmul(H2, {as_h2(M.z), as_h2(M.w)}), H4 = hmul(H3, {as_h2(N.z), as_h2(N.w)});
                mma_f16(acc[0], A, h.x, h.y);
                mma_f16(acc[1], A, as_u(H1.r), as_u(H1.i));
                mma_f16(acc[2], A, as_u(H2.r), as_u(H2.i));
                mma_f16(acc[3], A, as_u(H3.r), as_u(H3.i));
                mma_f16(acc[4], A, as_u(H4.r), as_u(H4.i));
            }
        }
        KSTAMP(10 + 3 * ps, z512.r);
    }
}

__device__ __forceinline__ void kgen_tables(const float (&acc)[5][4], uint32_t priv, int lane, float scale, float k0) {
    const int g = lane >> 2, t0 = lane & 1, t1 = (lane >> 1) & 1;
    __syncwarp();
    sts128(priv + 16 * lane + (lane < 17 ? T_PATCH - 48 : T_S4 + 608 - 272), 0, 0, 0, 0);
    if (lane < 20) sts128(priv + 16 * lane + (lane < 8 ? 0 : lane < 16 ? PLANE - 128 : T_DENSE - 256), 0, 0, 0, 0);
    uint32_t w2[2], w3[2], w4[2], ab[2], W[2], pv[2];
#pragma unroll
    for (int hf = 0; hf < 2; hf++) {
        const float k1 = acc[0][2 * hf] * scale, k2 = acc[0][2 * hf + 1] * scale, k3 = acc[1][2 * hf] * scale, k4 = acc[1][2 * hf + 1] * scale;
        w2[hf] = pack_bf16(k2, k1); w3[hf] = pack_bf16(k3, k2); w4[hf] = pack_bf16(k4, k3);
        ab[hf] = pack_bf16(acc[2][2 * hf + 1] * scale, acc[2][2 * hf] * scale);
        W[hf] = __byte_perm(w4[hf], ab[hf], 0x5410);
    }
    pv[1] = __shfl_xor_sync(0xffffffffu, t0 ? W[0] : W[1], 1);
    pv[0] = __shfl_sync(0xffffffffu, t0 ? W[1] : W[0], t0 ? lane - 1 : lane < 4 ? 31 - lane : lane - 3);
    const uint32_t kk = pack_bf16(k0, 0.f);
    if (lane == 0) pv[0] = __byte_perm(kk, pv[0], 0x5410);
    const uint32_t pd = priv + T_DENSE + 64 + 512 * t1 + 64 * g + 16 * t0;
#pragma unroll
    for (int hf = 0; hf < 2; hf++) {
        sts128(pd + 32 * hf, __byte_perm(w2[hf], pv[hf], 0x5432), w2[hf], w3[hf], w4[hf]);
        sts128(pd + 32 * hf + 1024, __byte_perm(pv[hf], 0, 0x3232), __byte_perm(ab[hf], pv[hf], 0x7632), ab[hf], __byte_perm(ab[hf], 0, 0x1010));
    }
    __syncwarp();
    if (lane == 31) {
        const uint32_t aa = __byte_perm(ab[1], 0, 0x1010);
        sts32(priv + T_DENSE + 60, kk);
        sts128(priv + T_PATCH - 64, aa, aa, aa << 16, 0u);
    }
}
__device__ __forceinline__ void kgen_tables2(const float (&acc)[5][4], uint32_t priv, int lane, float scale) {
    const int g = lane >> 2, t0 = lane & 1, t1 = (lane >> 1) & 1;
    const uint32_t p4 = priv + T_S4 + 16 * (6 + g + 8 * t1) + 4 * (t0 ^ 1), p8 = priv + T_S8 + 8 * (6 + g + 8 * t1 + 32 * t0);
#pragma unroll
    for (int i = 0; i < 4; i++) {
        sts16x2<18>(p4 + 256 * (i & 1) + 8 * (i >> 1), acc[3][i] * scale);
        sts16x2<10>(p8 + 128 * (i & 1) + 4 * (i >> 1), acc[4][i] * scale);
    }
    if (lane == 31) {
        const uint32_t c3 = pack_bf16(acc[3][3] * scale, 0.f);
        sts128(priv + T_PATCH + 48, c3, c3 * 0x10001u, c3 << 16, 0u);
    }
    __syncwarp();
}

__device__ __forceinline__ void ld_frag(uint32_t (&T)[4], uint32_t q) { T[0] = lds32(q); T[1] = lds32(q + 32); T[2] = lds32(q - 32); T[3] = lds32v(q); }
__device__ __forceinline__ void ld_swap(uint32_t (&T)[4], uint32_t q) { T[2] = lds32v(q); T[3] = lds32v(q + 32); T[0] = lds32v(q - 32); T[1] = lds32v(q); }
__device__ __forceinline__ void add_frag(uint32_t (&S)[4], const uint32_t (&E)[4], const uint32_t (&O)[4]) {
    S[0] = badd2(E[0], O[1]); S[1] = badd2(E[1], O[3]); S[2] = badd2(E[2], O[0]); S[3] = badd2(E[3], O[2]);
}
__device__ __forceinline__ void mma4(float* c, const uint32_t (&a)[4], uint32_t b0, uint32_t b1, bool first = false) {
    if (first) mma_bf16_z(c, a[0], a[1], a[2], a[3], b0, b1);
    else mma_bf16(c, a[0], a[1], a[2], a[3], b0, b1);
}
template <bool FIRST>
__device__ __forceinline__ void dense_step(float (&acc)[16][4], float (&B)[8][4], uint32_t (&T0)[4], uint32_t (&T1)[4], uint32_t (&R)[8][4],
                                           uint32_t pq, uint32_t va) {
    uint32_t T2[4], T3[4], S[4], s[8][2];
#pragma unroll
    for (int i = NPRE; i < 8; i++) ldsm4(R[i], va + i * 256);
    ld_frag(T2, pq + 1024); ld_swap(T3, pq + 1536);
    add_frag(S, T0, T1);
#pragma unroll
    for (int i = 0; i < 8; i++) {
        s[i][0] = badd2(R[i][0], R[i][3]); s[i][1] = badd2(R[i][1], R[i][2]);
        mma4(acc[2 * i], T0, R[i][0], R[i][1], FIRST);
        mma4(B[i], T1, R[i][2], R[i][3], FIRST);
        mma4(acc[2 * i + 1], S, s[i][0], s[i][1], FIRST);
    }
    ld_frag(T0, pq - 64); ld_swap(T1, pq + 448);
    add_frag(S, T2, T3);
#pragma unroll
    for (int i = 0; i < 7; i++) {
        if (!FIRST || i) mma4(acc[2 * i + 2], T2, R[i][0], R[i][1]);
        mma4(B[i + 1], T3, R[i][2], R[i][3]);
        mma4(acc[2 * i + 3], S, s[i][0], s[i][1]);
        if (i < NPRE) ldsm4(R[i], va + 16 + i * 256);
    }
}
template <class Wait, class After>
__device__ __forceinline__ void dense_phase(float (&acc)[16][4], uint32_t priv, int lane, Wait wait_for_tokens, After after_loop) {
    const int m = lane >> 3, r = lane & 7;
    const uint32_t pb = priv + T_DENSE + 4 * (15 + (lane >> 2) - 2 * (lane & 3));
    const uint32_t v8 = priv + 128 * (m >> 1) + 16 * r;
    float B[8][4];
    uint32_t T0[4], T1[4], R[8][4];
    uint32_t pq = pb + 512, va = v8 + PLANE * ((m ^ (m >> 1)) & 1);
    ld_frag(T0, pq); ld_swap(T1, pq + 512);
    wait_for_tokens();
#pragma unroll
    for (int i = 0; i < NPRE; i++) ldsm4(R[i], va + i * 256);
    dense_step<true>(acc, B, T0, T1, R, pq, va);
#pragma unroll 1
    do {
        pq -= 64; va += 16;
        dense_step<false>(acc, B, T0, T1, R, pq, va);
    } while (pq != pb + 64);
    after_loop();
    KSTAMP(14, as_h2(0u));
    const uint32_t pp = pb + T_PATCH - T_DENSE - 24;
    uint32_t N0[4], N1[4];
    ld_swap(T1, pb); ld_frag(N0, pp); ld_swap(N1, pp);
#pragma unroll
    for (int i = NPRE; i < 8; i++) ldsm4(R[i], va + 16 + i * 256);
#pragma unroll
    for (int i = 0; i < 8; i++)
#pragma unroll
        for (int j = 0; j < 4; j++) {
            acc[2 * i + 1][j] = (acc[2 * i + 1][j] - acc[2 * i][j]) - B[i][j];
            if (i) acc[2 * i][j] += B[i - 1][j];
        }
#pragma unroll
    for (int i = 0; i < 8; i++) {
        mma4(acc[2 * i], T0, R[i][0], R[i][1]);
        mma4(acc[2 * i + 1], T1, R[i][2], R[i][3]);
        if (i >= 4) {
            mma4(acc[2 * i], N0, R[i - 4][0], R[i - 4][1]);
            mma4(acc[2 * i + 1], N1, R[i - 4][2], R[i - 4][3]);
        }
    }
    const uint32_t b = v8 + PLANE + 112;
    const uint32_t bz = (m & 1) ? priv : b, bm = (m & 1) ? b : b + 512;
    const uint32_t M[4] = {lds32(pb + 4 * 520), lds32(pb + 4 * 528), lds32v(pp + 32), lds32(pp + 64)};
#pragma unroll
    for (int i = 0; i < 6; i++) {
        uint32_t V[4];
        ldsm4(V, i < 2 ? bz + ((m & 1) ? 0 : i * 256) : bm + (i - 2) * 256);
        mma4(acc[2 * i + 4], M, V[0], V[1]);
        mma4(acc[2 * i + 5], M, V[2], V[3]);
    }
}

__device__ __forceinline__ uint32_t ones2(int c, int lo, int n) {
    return (((uint32_t)(c - lo) < (uint32_t)n) ? 0x3f80u : 0u) | (((uint32_t)(c + 1 - lo) < (uint32_t)n) ? 0x3f800000u : 0u);
}
template <int L1, int N1, int L2, int N2, int D>
__device__ __forceinline__ void box_ones(uint32_t dst, int d) { sts128(dst, ones2(d, L1, N1), ones2(d, L2, N2), ones2(d + D, L1, N1), ones2(d + D, L2, N2)); }
__device__ __forceinline__ uint32_t tok_at(int T) { return PLANE * ((T >> 3) & 1) + 16 * ((T >> 4) + 8) + 2 * (T & 7); }
__device__ __forceinline__ float left_col(float cur, float prev, int lane) {
    return __shfl_sync(0xffffffffu, (lane & 3) == 3 ? prev : cur, lane + 3, 4);
}
struct Tails {
    uint4 q4, q8, B4[5], ad;
    uint2 B8[8];
    uint32_t W[2][4], A[2][2][4];
    float p1, p3, p8;
    static __host__ __device__ constexpr bool is8(int k) { return k >= 4 && (TORD ? (k & 1) : (k & 4) == 0); }
    static __host__ __device__ constexpr int grp(int k) { return k < 4 ? k : TORD ? (k - 4) / 2 + (is8(k) ? 0 : 4) : (k & 3) + 4 * ((k - 4) >> 3) + (is8(k) ? 0 : 4); }
    __device__ __forceinline__ void load(int k, uint32_t priv) {
        uint32_t* w = W[k & 1];
        const uint32_t o = priv + 128 * grp(k);
        if (is8(k)) {
            const uint2 vy = lds64(o + ad.w), vx = lds64(o + ad.z);
            w[0] = vy.x; w[1] = vy.y; w[2] = vx.x; w[3] = vx.y;
        } else { w[0] = lds32(o + ad.y); w[1] = lds32(o + ad.x + 16); w[2] = lds32(o + ad.x); w[3] = lds32v(o + ad.y); }
    }
    __device__ __forceinline__ void box(int k, int lane) {
        const uint32_t* w = W[k & 1];
        const uint4 q = is8(k) ? q8 : q4;
        uint32_t (&a)[2][4] = A[k & 1];
        float X[4], Y[4];
        mma_bf16_z(Y, q.x, q.y, q.z, q.w, w[0], w[1]);
        mma_bf16_z(X, q.x, q.y, q.z, q.w, w[2], w[3]);
        a[0][0] = pack_bf16(X[0], X[1]); a[0][1] = pack_bf16(Y[0], Y[1]);
        if (is8(k)) {
            a[0][2] = pack_bf16(left_col(Y[3], p8, lane), Y[2]); a[0][3] = pack_bf16(X[2], X[3]);
            p8 = Y[3];
        } else {
            a[0][2] = pack_bf16(X[2], X[3]); a[0][3] = pack_bf16(Y[2], Y[3]);
            a[1][0] = pack_bf16(left_col(Y[1], p1, lane), Y[0]); a[1][1] = pack_bf16v(X[0], X[1]);
            a[1][2] = pack_bf16(left_col(Y[3], p3, lane), Y[2]); a[1][3] = pack_bf16v(X[2], X[3]);
            p1 = Y[1]; p3 = Y[3];
        }
    }
    __device__ __forceinline__ void taps(int k, float (&acc)[16][4]) {
        const int G = grp(k);
        if (is8(k)) {
#pragma unroll
            for (int b = 0; b < 8; b++) if (G + 8 + b < 16) mma4(acc[G + 8 + b], A[k & 1][0], B8[b].x, B8[b].y);
        } else {
#pragma unroll
            for (int b = 0; b < 5; b++) if (G + 4 + b < 16) mma4(acc[G + 4 + b], A[k & 1][0], B4[b].x, B4[b].y);
#pragma unroll
            for (int b = 0; b < 5; b++) if (G + 4 + b < 16) mma4(acc[G + 4 + b], A[k & 1][1], B4[b].z, B4[b].w);
        }
    }
    __device__ __forceinline__ void start(uint32_t lc, uint32_t priv, uint32_t tap, int lane) {
        ad = lds128(lc + 1024); q4 = lds128(lc); q8 = lds128(lc + 512);
        p1 = p3 = p8 = 0.f;
        load(0, priv); load(1, priv);
#pragma unroll
        for (int i = 0; i < 5; i++) B4[i] = lds128(priv + T_S4 + 128 * i + 2 * tap);
        box(0, lane);
    }
    template <int K0, int K1>
    __device__ __forceinline__ void run(float (&acc)[16][4], uint32_t priv, uint32_t tap, int lane) {
#pragma unroll
        for (int k = K0; k < K1; k++) {
            if (k + 2 < 20) load(k + 2, priv);
            if (k == 4) {
#pragma unroll
                for (int i = 0; i < 8; i++) B8[i] = lds64(priv + T_S8 + 64 * i + tap);
            }
            if (k + 1 < 20) box(k + 1, lane);
            taps(k, acc);
        }
    }
};
__device__ __forceinline__ void lane_consts(uint32_t dst, int unit, int lane) {
    const int g = lane >> 2, t = lane & 3, m = lane >> 3, r = lane & 7;
    if (unit == 0) box_ones<0, 5, 5, 3, 8>(dst, 2 * t - g);
    else if (unit == 1) box_ones<1, 7, 0, 9, 2>(dst, 4 * t - g);
    else if (unit == 2) sts128(dst, tok_at(16 * g - 10 + 2 * t), tok_at(16 * g - 2 + 2 * t), tok_at(16 * g - 12 + 4 * t), tok_at(16 * g - 4 + 4 * t));
    else {
        const uint32_t low = 64 * (t >> 1) + 32 * (g & 1) + 16 * (t & 1), hi = (lane & 24) + (lane & 16);
        sts128(dst, 128 * hi + low, 512 * (4 * (r & 2) + 2 * m + (r & 1)) + 16 * ((r >> 2) ^ (2 * (r & 3))), 32 * hi + low, 8 * (6 + g - 2 * t));
    }
}

__device__ __forceinline__ uint32_t mean_std(float mu, float var) { return pack_bf16(mu, sqrtaf(bf_round(bf_round(var) + 1e-5f))); }
__device__ __noinline__ uint2 ln_centred(uint32_t sb, float mu) {
    const int lane = threadIdx.x & 31;
    uint32_t ms = 0;
    float res = 0.f, ri = 0.f;
#pragma unroll 1
    for (int mode = 0; mode < 2; mode++) {
#pragma unroll 1
        for (int rr = 0; rr < 16; rr++) {
            const float c0 = __shfl_sync(0xffffffffu, mu, rr), rj = __shfl_sync(0xffffffffu, ri, rr);
            float c = 0.f;
#pragma unroll 1
            for (int k = 0; k < 16; k++) {
                const uint32_t q = lds32(sb + OFF_ROWS + k * 2048 + rr * 128 + ((lane * 4) ^ ((rr & 7) << 4))), wq = lds32(sb + OFF_GP + k * 128 + lane * 4);
                const float d0 = bf_lo(q) - c0, d1 = bf_hi(q) - c0;
                if (mode) c = fmaf(bf_round(bf_round(d0) * rj), bf_lo(wq), fmaf(bf_round(bf_round(d1) * rj), bf_hi(wq), c));
                else c = fmaf(d0, d0, fmaf(d1, d1, c));
            }
#pragma unroll 1
            for (int o = 16; o; o >>= 1) c += __shfl_xor_sync(0xffffffffu, c, o);
            if ((lane & 15) == rr) res = c;
        }
        if (mode == 0) { ms = mean_std(mu, res * (1.f / DM)); mu = bf_lo(ms); ri = rcpf(bf_hi(ms)); }
    }
    named_sync(1, 128);
    return make_uint2(ms, __float_as_uint(res));
}

__device__ __forceinline__ void router_cta(uint32_t* scr, uint32_t sb, uint32_t zero, int tid, int warp) {
    const int lane = tid & 31;
    const uint32_t cand = sb + 128;
    const uint32_t epoch = ld_relaxed_32(scr + S_EPOCH);
    if (tid < 128) st_relaxed_32(scr + S_SEL + tid, 0u);
    if (tid == 0) sts32(sb + 64, cand);
    sts128(cand + 16 * tid, 0, 0, 0, 0);
    asm volatile("fence.acq_rel.gpu;" ::: "memory");
    const uint32_t tag = (epoch + 1u) | 0x8000u;
    STAMP(0); GSTAMP(1);
    uint32_t* const psel = scr + S_SEL + 32 * (lane & 3);
    const uint32_t cnt = sb + 64 + (tid & zero);
    uint32_t it = 0;
    uint4 q;
#pragma unroll 1
    do {
        q = ld_relaxed_128(scr + S_KEY + 4 * tid);
        if (++it > SPIN_LIMIT) __trap();
    } while (!__all_sync(0xffffffffu, (((q.x ^ tag) | (q.y ^ tag) | (q.z ^ tag) | (q.w ^ tag)) & 0xffffu) == 0));
    STAMP(2);
    uint32_t key[4] = {q.x, q.y, q.z, q.w};
#pragma unroll
    for (int j = 0; j < 4; j++) key[j] = ((key[j] ^ ((uint32_t)((int)key[j] >> 31) | 0x80000000u)) & 0xffff0000u) | (0xffffu - (uint32_t)(4 * tid + j));
    const uint32_t gm = __reduce_max_sync(0xffffffffu, max(max(key[0], key[1]), max(key[2], key[3])));
    sts32(sb + 4 * warp, gm);
    __syncthreads();
    const uint2 pr = lds64(sb + 8 * (lane & 7));
    const uint32_t tau = __reduce_min_sync(0xffffffffu, max(pr.x, pr.y));
    asm volatile("{\n\t.reg .pred p<4>;\n\t.reg .u32 a<4>;\n\t"
                 "setp.ge.u32 p0, %0, %4;\n\tsetp.ge.u32 p1, %1, %4;\n\tsetp.ge.u32 p2, %2, %4;\n\tsetp.ge.u32 p3, %3, %4;\n\t"
                 "@p0 atom.shared.add.u32 a0, [%5], 4;\n\t@p1 atom.shared.add.u32 a1, [%5], 4;\n\t"
                 "@p2 atom.shared.add.u32 a2, [%5], 4;\n\t@p3 atom.shared.add.u32 a3, [%5], 4;\n\t"
                 "@p0 st.shared.u32 [a0], %0;\n\t@p1 st.shared.u32 [a1], %1;\n\t@p2 st.shared.u32 [a2], %2;\n\t@p3 st.shared.u32 [a3], %3;\n\t}"
                 ::"r"(key[0]), "r"(key[1]), "r"(key[2]), "r"(key[3]), "r"(tau), "r"(cnt) : "memory");
    __syncthreads();
    STAMP(6);
    const uint32_t c0 = lds32v(cand + 4 * lane);
    uint2 k = lds64(cand + 8 * warp);
    const uint32_t end = __shfl_sync(0xffffffffu, lds32v(sb + 64), 0);
    uint32_t i = cand + 8 * warp;
#pragma unroll 1
    do {
        uint32_t r0 = __popc(__ballot_sync(0xffffffffu, c0 > k.x)), r1 = __popc(__ballot_sync(0xffffffffu, c0 > k.y));
#pragma unroll 1
        for (uint32_t j = cand + 128; j < end; j += 128) {
            const uint32_t c = lds32(j + 4 * lane);
            r0 += __popc(__ballot_sync(0xffffffffu, c > k.x)); r1 += __popc(__ballot_sync(0xffffffffu, c > k.y));
        }
        const uint32_t rk = (lane & 4) ? r1 : r0;
        if (rk < 8 && lane < 8) st_relaxed_64(psel + 2 * rk, (lane & 4) ? k.y : k.x, tag);
        i += 128;
        k = lds64(i);
    } while (i < end);
    STAMP(4); GSTAMP(5);
    if (tid == 0) st_relaxed_32(scr + S_EPOCH, epoch + 1u);
}

__global__ void __cluster_dims__(2, 1, 1) __launch_bounds__(NTHR, 1)
fused_kernel(const __grid_constant__ Ptrs p, const __grid_constant__ Maps maps) {
    extern __shared__ __align__(1024) unsigned char smem[];
    const uint32_t sb = s_u32(smem);
    const int tid = threadIdx.x, lane = tid & 31;
    const int warp = __shfl_sync(0xffffffffu, tid >> 5, 0);
    const int b = blockIdx.x, h = b & 1, cl = b >> 1;
    const uint32_t bar0 = sb + OFF_BAR;
    const int m = lane >> 3, r = lane & 7;
    if (b >= NCTA) {
        if (b == NCTA) router_cta(p.scr, sb, p.zero, tid, warp);
        return;
    }
    if (warp < 8) {
        const int w = warp, dch = 8 * b + w;
        STAMP(0);
        if (INC_AT == 0) asm volatile("setmaxnreg.inc.sync.aligned.u32 %0;" ::"n"(NREG));
        const int po = dch * NMODE + 4 * lane;
        const uint2 la = ldg64(p.logA + po), aim = ldg64(p.Aim + po), cre = ldg64(p.Cre + po), cim = ldg64(p.Cim + po);
        const uint32_t ldt16 = ldg16(p.ldt + dch), dsk16 = ldg16(p.dsk + dch);
        cluster_arrive();
        if (CW_EARLY) cluster_wait();
        if (INC_AT == 1) asm volatile("setmaxnreg.inc.sync.aligned.u32 %0;" ::"n"(NREG));
        const uint32_t priv = sb + OFF_PRIV + w * PRIV;
        const int g = lane >> 2, t = lane & 3;
        float kacc[5][4], kscale;
        {
            const uint32_t m2 = as_u(__hmax2(__hmax2(__habs2(as_b2(cre.x)), __habs2(as_b2(cre.y))), __hmax2(__habs2(as_b2(cim.x)), __habs2(as_b2(cim.y)))));
            const uint32_t eb = min(max(__reduce_max_sync(0xffffffffu, max(m2 << 16, m2)) >> 23, 1u), 252u);
            const float dt = bf_round(ex2f(bf_lo(ldt16) * L2E));
            STAMP(1);
            kgen_mma(kacc, priv, lane, la, aim, cre, cim, dt, (253u - eb) * 0x00800080u);
            STAMP(2);
            if (INC_AT == 2) asm volatile("setmaxnreg.inc.sync.aligned.u32 %0;" ::"n"(NREG));
            if (!CW_EARLY) cluster_wait();
            __syncwarp();
            if (elect_one()) mbar_arrive(bar0 + 8 * B_KG);
            float s0[4];
            mma_bf16_z(s0, ONES, ONES, ONES, ONES, cre.x, cre.y);
            float k0 = s0[0] + s0[1];
            k0 += __shfl_xor_sync(0xffffffffu, k0, 1);
            k0 += __shfl_xor_sync(0xffffffffu, k0, 2);
            kscale = (dt + dt) * __uint_as_float((eb + 1u) << 23);
            kgen_tables(kacc, priv, lane, kscale, fmaf(k0, dt + dt, bf_lo(dsk16) + 1.f));
        }
        STAMP(3);
        if (INC_AT == 3) { __syncwarp(); asm volatile("setmaxnreg.inc.sync.aligned.u32 %0;" ::"n"(NREG)); }
        kgen_tables2(kacc, priv, lane, kscale);
        STAMP(4);
        if (INC_AT == 4) asm volatile("setmaxnreg.inc.sync.aligned.u32 %0;" ::"n"(NREG));
        float acc[16][4];
        dense_phase(acc, priv, lane, [&]() {
            mbar_wait(bar0 + 8 * B_VT, 0);
            STAMP(6);
        }, [&]() { mbar_wait(bar0 + 8 * B_PV, 0); });
        STAMP(7);
        const uint32_t sd = sb + OFF_X + 512 * (8 * h + w) + 16 * (lane ^ (2 * (w & 1) + 4 * h));
        const uint32_t sd0 = mapa(sd + 8192, 0), sd1 = mapa(sd, 1);
        auto send = [&](auto PT) {
            constexpr int pt = decltype(PT)::value;
#pragma unroll
            for (int i = 0; i < 2; i++) {
                const float* c0 = acc[4 * pt + 2 * i];
                const float* c1 = acc[4 * pt + 2 * i + 1];
                asm volatile("st.async.weak.shared::cluster.mbarrier::complete_tx::bytes.v4.b32 [%0 + %6], {%1,%2,%3,%4}, [%5];"
                             ::"r"(i ? sd1 : sd0), "r"(pack_bf16(c0[0], c0[1])), "r"(pack_bf16(c0[2], c0[3])), "r"(pack_bf16(c1[0], c1[1])),
                               "r"(pack_bf16(c1[2], c1[3])), "r"(mapa(bar0 + 8 * (B_RECV + pt), i)), "n"(16384 * pt) : "memory");
            }
        };
        const uint4 lc = lds128(sb + OFF_LC + 1536 + 16 * lane);
        const uint32_t stg = (priv + T_DENSE + 63) & ~127u, so = stg + lc.z;
        const uint32_t xa = sb + OFF_X + 16384 * (w >> 2) + 8192 * h + 256 * (w & 3) + lc.x;
        const uint32_t sa = sb + OFF_X + 16384 * (w >> 2) + 8192 * (h ^ 1) + 128 * (w & 3) + lc.y;
        constexpr int ST2 = -2048;
        auto finish = [&](int ph) {
            if (ph == FINE) STAMP(1);
            const int box = 4 * ph + 2 * (w >> 2) + h;
            uint4 x[4];
            uint32_t s[4][4];
#pragma unroll
            for (int i = 0; i < 4; i++) x[i] = lds128((xa ^ (8 * (i & 2))) + 32768 * ph + 2048 * (i & 1) + 64 * (i & 2));
            if (ph == FINE) STAMP(2);
            mbar_wait(bar0 + 8 * (B_RECV + 2 * ph + (w >> 2)), 0);
            if (ph == FINE) STAMP(3);
            const uint32_t routed = __shfl_sync(0xffffffffu, lds32(sb + OFF_MISC + 4), 0);
#pragma unroll
            for (int i = 0; i < 4; i++) ldsm4t(s[i], (sa ^ (32 * i)) + 32768 * ph);
#pragma unroll
            for (int i = 0; i < 4; i++) { s[i][0] = badd2(x[i].x, s[i][0]); s[i][1] = badd2(x[i].y, s[i][1]); s[i][2] = badd2(x[i].z, s[i][2]); s[i][3] = badd2(x[i].w, s[i][3]); }
            if (ph == FINE) STAMP(4);
            if (((routed >> (4 * box + (w & 3))) & 1) || (LAST_DIRECT && ph && w >= 4)) {
                const uint32_t tk = 256 * box + 128 * (g >> 2) + 32 * (t >> 1) + 16 * (g & 1) + 4 * (g & 2) + 2 * (w & 3);
                const uint32_t mk[2] = {lds32(sb + OFF_MISC + 32 + 4 * (tk >> 5)) >> (tk & 31), lds32(sb + OFF_MISC + 40 + 4 * (tk >> 5)) >> (tk & 31)};
                __nv_bfloat16* o = p.out + (size_t)tk * DM + 16 * cl + 8 * (t & 1);
#pragma unroll
                for (int i = 0; i < 4; i++)
                    asm volatile("{\n\t.reg .pred p;\n\tsetp.eq.u32 p, %6, 0;\n\t@!p st.shared.v4.u32 [%1], {%2,%3,%4,%5};\n\t@p st.global.v4.u32 [%0], {%2,%3,%4,%5};\n\t}"
                                 ::"l"(o + (64 * (i & 1) + (i >> 1)) * DM), "r"((xa ^ (8 * (i & 2))) + 32768 * ph + 2048 * (i & 1) + 64 * (i & 2)),
                                   "r"(s[i][0]), "r"(s[i][1]), "r"(s[i][2]), "r"(s[i][3]), "r"(mk[i & 1] & (1u << (i >> 1))) : "memory");
            } else {
#pragma unroll
                for (int i = 0; i < 4; i++) sts128(so + ST2 * ph + 512 * (i & 1) + 64 * (i & 2), s[i][0], s[i][1], s[i][2], s[i][3]);
                fence_async();
                if (ph == FINE) STAMP(5);
                __syncwarp();
                if (elect_one()) {
                    asm volatile("cp.async.bulk.tensor.5d.global.shared::cta.bulk_group [%0, {%2, %5, %3, %5, %4}], [%1];"
                                 ::"l"(&maps.out), "r"(stg + ST2 * ph), "r"(16 * cl), "r"(2 * (w & 3)), "r"(4 * box), "r"(0) : "memory");
                }
            }
        };
        Tails tl;
        tl.start(sb + OFF_LC + 16 * lane, priv, lc.w, lane);
        send(IC<0>());
        tl.run<0, 4>(acc, priv, lc.w, lane);
        send(IC<1>());
        STAMP(8);
        tl.run<4, FIN_A>(acc, priv, lc.w, lane);
        if (FIN_A == FIN_B || w < 4) finish(0);
        tl.run<FIN_A, FIN_B>(acc, priv, lc.w, lane);
        if (FIN_A != FIN_B && FIN_B < 12 && w >= 4) finish(0);
        tl.run<FIN_B, 12>(acc, priv, lc.w, lane);
        send(IC<2>());
        STAMP(9);
        if (FIN_A != FIN_B && FIN_B == 12 && w >= 4) finish(0);
        tl.run<12, 20>(acc, priv, lc.w, lane);
        STAMP(11);
        send(IC<3>());
        finish(1);
        STAMP(12);
        __syncwarp();
        if (elect_one()) mbar_arrive(bar0 + 8 * B_ST);
        cluster_arrive();
        asm volatile("cp.async.bulk.commit_group;" ::: "memory");
        asm volatile("cp.async.bulk.wait_group.read 0;" ::: "memory");
        STAMP(13); GSTAMP(15);
    } else if (warp < 12) {
        const int a = warp - 8, at = 32 * a + lane, g = lane >> 2, t = lane & 3;
        STAMP(0);
        if (elect_one()) {
            const uint32_t cnt = a == 3 ? 0x18411122u : a == 2 ? 0x44444444u : 0x11111111u, tx = a == 0 ? 0x44444444u : a == 3 ? 0x00084444u : 0u;
#pragma unroll 1
            for (int i = 0; i < 8; i++) {
                mbar_init(bar0 + 64 * a + 8 * i, (cnt >> (4 * i)) & 15);
                const uint32_t n = (tx >> (4 * i)) & 15;
                if (n) mbar_expect_tx(bar0 + 64 * a + 8 * i, n << 11);
            }
            if (a < 3) mbar_init(bar0 + 8 * (B_KG + a), a ? 4 : 8);
            asm volatile("fence.mbarrier_init.release.cluster;" ::: "memory");
            fence_async();
        }
        __syncwarp();
        cluster_arrive();
        if (FREG > 128) asm volatile("setmaxnreg.inc.sync.aligned.u32 %0;" ::"n"(FREG));
        const uint32_t epoch = ld_relaxed_32(p.scr + S_EPOCH);
        uint32_t* const pst = p.scr + S_STAT + 2048 * a + 16 * b + 2 * r + m;
        uint32_t* const pky = p.scr + S_KEY + 16 * b + at;
        if (at < 16) st_relaxed_32(pky, 0u);
        uint32_t* const py = p.scr + S_Y + 1024 * ((cl & ~3) + a) + 128 * (b & 7) + 32 * t + 4 * g;
        const uint32_t gp = sb + OFF_GP;
        sts32(gp + 2048 + 4 * lane, ONES);
        lane_consts(sb + OFF_LC + 16 * at, a, lane);
        cluster_wait();
        STAMP(1);
        if (lane < 16) st_relaxed_32(pst, epoch << 31);
        mbar_wait(bar0 + 8 * B_WR, 0);
        float wsum;
        {
            const uint4 q = lds128(gp + 16 * at);
            wsum = ((bf_lo(q.x) + bf_hi(q.x)) + (bf_lo(q.y) + bf_hi(q.y))) + ((bf_lo(q.z) + bf_hi(q.z)) + (bf_lo(q.w) + bf_hi(q.w)));
#pragma unroll
            for (int o = 16; o; o >>= 1) wsum += __shfl_xor_sync(0xffffffffu, wsum, o);
            sts32(gp + 2176 + 4 * a, __float_as_uint(wsum));
        }
        const uint32_t hsel = (epoch & 1) * (GU_CTAS * 128), want = (epoch & 1) ? 0u : 0x80008000u;
        const uint32_t tbit = ~epoch << 31, ktag = ((epoch + 1u) | 0x8000u) & 0xffffu;
        if (a == 0) sts64(sb + OFF_MISC + 32 + 8 * lane, 0u, 0u);
        if (b < GU_CTAS) st_relaxed_32(p.scr + S_H + (GU_CTAS * 128 - hsel) + b * 128 + at, 0u);
        {
            uint32_t ra[4], rb[4], rs;
#pragma unroll
            for (int i = 0; i < 4; i++) {
                ra[i] = (m & 1) ? (r == 1 ? gp + 128 * a + 32 * i + 16 * (m >> 1) : gp + 2048) : sb + OFF_ROWS + 2048 * a + 128 * r + (((2 * i + (m >> 1)) ^ r) << 4);
                rb[i] = sb + OFF_ROWS + 2048 * a + 128 * (r + 8 * (m >> 1)) + (((2 * i + (m & 1)) ^ r) << 4);
            }
            rs = (m & 1) ? (r == 1 ? 512 : 0) : 8192;
            const uint32_t r8 = (m & 1) ? 0 : 1024;
            float cs[4][4] = {};
#pragma unroll 1
            for (int k = 0; k < 4; k++) {
                uint32_t x[4][4], y[4][4], z[4][4];
                mbar_wait(bar0 + 8 * (B_ROW + k), 0);
#pragma unroll
                for (int i = 0; i < 4; i++) {
                    ldsm4(x[i], ra[i]); ldsm4(y[i], ra[i] + r8);
                    if (LN_DUP) ldsm4(z[i], rb[i] + 8192 * k);
                    else { z[i][0] = x[i][0]; z[i][1] = x[i][2]; z[i][2] = y[i][0]; z[i][3] = y[i][2]; }
                    ra[i] += rs;
                }
#pragma unroll
                for (int i = 0; i < 4; i++) {
                    mma4(cs[2 * (i & 1)], x[i], z[i][0], z[i][1]);
                    mma4(cs[2 * (i & 1) + 1], y[i], z[i][2], z[i][3]);
                }
            }
            const uint32_t pa = gp + 2304 + 4 * a;
#pragma unroll
            for (int i = 0; i < 8; i++) cs[i >> 2][i & 3] += cs[2 + (i >> 2)][i & 3];
            if (g < 2) {
#pragma unroll
                for (int i = 0; i < 4; i++) sts32(pa + 256 * g + 32 * t + 128 * (i >> 1) + 16 * (i & 1), __float_as_uint(cs[i >> 1][2 + (i & 1)]));
            }
            if (t == (g >> 1)) {
                sts32(pa + 512 + 16 * g, __float_as_uint((g & 1) ? cs[0][1] : cs[0][0]));
                sts32(pa + 640 + 16 * g, __float_as_uint((g & 1) ? cs[1][1] : cs[1][0]));
            }
            named_sync(1, 128);
            auto sum4 = [](uint4 q) { return (__uint_as_float(q.x) + __uint_as_float(q.y)) + (__uint_as_float(q.z) + __uint_as_float(q.w)); };
            const uint32_t o = gp + 2304 + 16 * (lane & 15);
            const float mu = sum4(lds128(o)) * (1.f / DM), e2 = sum4(lds128(o + 512)) * (1.f / DM), var = fmaf(-mu, mu, e2);
            const float sw = sum4(lds128(o + 256));
            wsum = sum4(lds128(gp + 2176));
            uint32_t ms = mean_std(mu, var);
            float sc = (sw - bf_round(mu) * wsum) * rcpf(bf_hi(ms));
            if (__any_sync(0xffffffffu, !(e2 <= 65.f * var))) {
                const uint2 c = ln_centred(sb, mu);
                ms = c.x; sc = __uint_as_float(c.y);
            }
            if (lane < 16) st_relaxed_32(pst, ms | tbit);
            if (at < 16) st_relaxed_32(pky, pack_bf16(0.f, sc) | ktag);
            if (lane < 8) mbar_arrive(bar0 + 8 * (B_EMPTY + lane));
        }
        STAMP(3); GSTAMP(14);
        {
            const uint32_t* sp = p.scr + S_STAT + 2048 * (cl & 3) + 512 * a + 16 * t + 2 * g;
            uint2 sq[8];
            uint32_t s2[8], bad;
            if (ST_GATE >= 0) mbar_wait(bar0 + 8 * (B_X + 4 * h + ST_GATE), 0);
#pragma unroll 1
            do {
                __nanosleep(STAT_SLEEP);
#pragma unroll
                for (int i = 0; i < 8; i++) sq[i] = ld_relaxed_64(sp + 64 * i);
                bad = 0;
#pragma unroll
                for (int i = 0; i < 8; i++) { s2[i] = __byte_perm(sq[i].x, sq[i].y, 0x7632) ^ want; bad |= s2[i]; }
            } while (!__all_sync(0xffffffffu, (bad & 0x80008000u) == 0));
            STAMP(13);
            const uint32_t xa = sb + OFF_X + 16384 * a + 32 * lane + ((h ^ (g & 1)) << 4);
            const uint32_t dst = sb + OFF_PRIV + (2 * m + (r & 1)) * PRIV + 128 + 512 * a + 16 * (r >> 1);
#pragma unroll
            for (int bk = 0; bk < 2; bk++) {
                mbar_wait(bar0 + 8 * (B_X + 2 * a + bk), 0);
                uint32_t v[8][4];
#pragma unroll
                for (int i = 0; i < 4; i++) {
                    const uint2 rc = recip2(s2[4 * bk + i]), st = sq[4 * bk + i];
#pragma unroll
                    for (int hf = 0; hf < 2; hf++) {
                        const __nv_bfloat162 mm = __low2bfloat162(as_b2(hf ? st.y : st.x));
                        const __nv_bfloat162 rh = hf ? __high2bfloat162(as_b2(rc.x)) : __low2bfloat162(as_b2(rc.x));
                        const __nv_bfloat162 rl = hf ? __high2bfloat162(as_b2(rc.y)) : __low2bfloat162(as_b2(rc.y));
                        const uint4 q = lds128(xa + 8192 * bk + 2048 * i + 1024 * hf);
                        uint32_t* o = v[2 * i + hf];
                        o[0] = normalize2(q.x, mm, rh, rl); o[1] = normalize2(q.y, mm, rh, rl); o[2] = normalize2(q.z, mm, rh, rl); o[3] = normalize2(q.w, mm, rh, rl);
                    }
                }
                if (bk == 0) mbar_wait(bar0 + 8 * B_KG, 0);
#pragma unroll
                for (int i = 0; i < 8; i++) stsm4t(dst + 256 * bk + 64 * (i >> 1) + PLANE * (i & 1), v[i]);
            }
            __syncwarp();
            if (elect_one()) { mbar_arrive(bar0 + 8 * B_VT); mbar_arrive_peer(mapa(bar0 + 8 * B_PV, h ^ 1)); }
            __syncwarp();
            cluster_arrive();
        }
        uint32_t mykey;
        {
            const uint32_t* sl = p.scr + S_SEL + 32 * (cl & 3) + 2 * g;
            uint2 q;
#pragma unroll 1
            do {
                __nanosleep(SEL_SLEEP);
                q = ld_relaxed_64(sl);
            } while (!__all_sync(0xffffffffu, q.y == ((epoch + 1u) | 0x8000u)));
            mykey = q.x;
        }
        STAMP(4);
        if (a == 0) {
            const uint32_t tok = ~mykey & 0xffffu;
            if (t == 0) asm volatile("red.shared.or.b32 [%0], %1;" ::"r"(sb + OFF_MISC + 32 + 4 * (tok >> 5)), "r"(1u << (tok & 31u)) : "memory");
            sts32(sb + OFF_MISC + 4, __reduce_or_sync(0xffffffffu, 1u << (4 * (tok >> 8) + ((tok >> 1) & 3))));
            __syncwarp();
            if (elect_one()) { mbar_arrive(bar0 + 8 * B_RECV); mbar_arrive(bar0 + 8 * (B_RECV + 1)); }
        }
        if (b < GU_CTAS) {
            const uint32_t tok = 0xffffu - (mykey & 0xffffu);
            {
                const uint32_t tk = __shfl_sync(0xffffffffu, tok, 16 * h + 4 * a);
                if (elect_one())
                    asm volatile("cp.async.bulk.shared::cluster.global.mbarrier::complete_tx::bytes.multicast::cluster [%0], [%1], 2048, [%2], %3;"
                                 ::"r"(sb + OFF_XS + (4 * h + a) * ROW_PITCH), "l"(p.u + (size_t)tk * DM), "r"(bar0 + 8 * B_XS), "h"((uint16_t)3) : "memory");
            }
            uint2 rec;
#pragma unroll 1
            do {
                rec = ld_relaxed_64(p.scr + S_STAT + 2048 * a + (tok & ~15u) + 2 * (tok & 7u));
            } while (!__all_sync(0xffffffffu, ((__byte_perm(rec.x, rec.y, 0x7632) ^ want) & 0x80008000u) == 0));
            const uint32_t mst = (tok & 8u) ? rec.y : rec.x;
            const uint32_t m2 = __byte_perm(mst, 0, 0x1010);
            const float rs = rcpf(__uint_as_float(mst & 0x7fff0000u));
            const float r0 = __shfl_sync(0xffffffffu, rs, 8 * t), r1 = __shfl_sync(0xffffffffu, rs, 8 * t + 4);
            float gacc[4 * NACC][4] = {};
            const int k = r + 8 * (m >> 1);
            uint32_t wa[4];
#pragma unroll
            for (int mt = 0; mt < 4; mt++) wa[mt] = 1024 * a + (((m & 1) * 4096) ^ p.up_first) + k * 64 + ((((k >> 1) & 3) ^ mt) << 4);
            const uint32_t xa = sb + OFF_XS + r * ROW_PITCH + 32 * a + 16 * (m & 1) + 128 * (m >> 1);
#pragma unroll 1
            for (int c = 0; c < 4; c++) {
                uint32_t af[4][4][4], xb[2][4];
                const uint32_t half = sb + OFF_RING + 32768 * (c & 1), fb = bar0 + 8 * B_FULL + 32 * (c & 1);
#pragma unroll
                for (int j = 0; j < 4; j++) {
                    mbar_wait(fb + 8 * j, c >> 1);
                    if (j == 3) STAMP(12);
#pragma unroll
                    for (int mt = 0; mt < 4; mt++) ldsm4t(af[j][mt], wa[mt] + half + j * 8192);
                    __syncwarp();
                    if (elect_one()) mbar_arrive(fb + 8 * (B_EMPTY - B_FULL + j));
                    if (j == GU_SPLIT) {
                        mbar_wait(bar0 + 8 * B_XS, 0);
#pragma unroll
                        for (int i = 0; i < 2; i++) {
                            ldsm4(xb[i], xa + 512 * c + 256 * i);
#pragma unroll
                            for (int e = 0; e < 4; e++) xb[i][e] = as_u(__hsub2(as_b2(xb[i][e]), as_b2(m2)));
                        }
                    }
                    if (j == 3) STAMP(1);
                    if (j >= GU_SPLIT) {
#pragma unroll
                        for (int ks = j == GU_SPLIT ? 0 : j; ks <= j; ks++) {
#pragma unroll
                            for (int mt = 0; mt < 4; mt++)
                                mma_bf16v(gacc[mt + 4 * (ks % NACC)], af[ks][mt], xb[ks >> 1][2 * (ks & 1)], xb[ks >> 1][2 * (ks & 1) + 1]);
                        }
                    }
                }
            }
            STAMP(6);
#pragma unroll
            for (int mt = 0; mt < 4; mt++) {
#pragma unroll
                for (int i = 0; i < 4 * (NACC - 1); i++) gacc[mt][i] += gacc[mt + 4][i];
                sts128f(gp + 2048 * a + mt * 512 + lane * 16, gacc[mt]);
            }
            named_sync(1, 128);
            {
                uint4 q[4];
#pragma unroll
                for (int wq = 0; wq < 4; wq++) q[wq] = lds128(gp + 2048 * wq + 16 * at);
                const uint32_t g2 = pack_bf16(r0 * ((__uint_as_float(q[0].x) + __uint_as_float(q[1].x)) + (__uint_as_float(q[2].x) + __uint_as_float(q[3].x))),
                                              r1 * ((__uint_as_float(q[0].y) + __uint_as_float(q[1].y)) + (__uint_as_float(q[2].y) + __uint_as_float(q[3].y))));
                const uint32_t u2 = pack_bf16(r0 * ((__uint_as_float(q[0].z) + __uint_as_float(q[1].z)) + (__uint_as_float(q[2].z) + __uint_as_float(q[3].z))),
                                              r1 * ((__uint_as_float(q[0].w) + __uint_as_float(q[1].w)) + (__uint_as_float(q[2].w) + __uint_as_float(q[3].w))));
                const uint32_t s2 = pack_bf16(bf_lo(g2) * rcpf(1.f + ex2f(-L2E * bf_lo(g2))), bf_hi(g2) * rcpf(1.f + ex2f(-L2E * bf_hi(g2))));
                uint32_t hw;
                asm volatile("movmatrix.sync.aligned.m8n8.trans.b16 %0, %1;" : "=r"(hw) : "r"(as_u(__hmul2(as_b2(s2), as_b2(u2)))));
                if (hw == 0u) hw = 0x80008000u;
                st_relaxed_32(p.scr + S_H + hsel + b * 128 + at, hw);
            }
            STAMP(7);
        }
        const uint32_t ytag = 1u + (epoch & 1);
        {
            const uint32_t* hp = p.scr + S_H + hsel + (b & 7) * 1792 + 64 * a + lane;
            uint32_t wa[4], af[DN_RUN][4][4], hb[14];
#pragma unroll
            for (int mt = 0; mt < 4; mt++) wa[mt] = sb + OFF_RING + 2048 * a + 128 * (r + 8 * (m >> 1)) + (((2 * mt + (m & 1)) ^ r) << 4);
            float dacc[4][4] = {};
            auto load_w = [&](int s) {
                mbar_wait(bar0 + 8 * (B_FULL + s), 0);
#pragma unroll
                for (int j = 0; j < 4; j++) ldsm4t(af[s % DN_RUN][j], wa[j] + s * 8192);
            };
            auto run = [&](int s) {
#pragma unroll
                for (int j = 0; j < 4; j++) mma_bf16v(dacc[j], af[s % DN_RUN][j], hb[2 * s], hb[2 * s + 1]);
            };
            auto look = [&]() {
#pragma unroll
                for (int j = 0; j < 14; j++) hb[j] = ld_relaxed_32(hp + 256 * (j >> 1) + 32 * (j & 1));
            };
            auto missing = [&]() {
                uint32_t mn = hb[0];
#pragma unroll
                for (int j = 1; j < 14; j++) mn = min(mn, hb[j]);
                return __any_sync(0xffffffffu, mn == 0);
            };
            load_w(0);
            st_relaxed_128(py, 0u, 0u, 0u, 0u);
            bool again = true;
            if (b >= GU_CTAS) { look(); again = missing(); }
#pragma unroll
            for (int s = 1; s < DN_PRE; s++) load_w(s);
            if (again) look();
#pragma unroll
            for (int s = DN_PRE; s < DN_RUN; s++) load_w(s);
#pragma unroll 1
            while (missing()) { __nanosleep(H_SLEEP); look(); }
            STAMP(2);
#pragma unroll
            for (int s = 0; s < DN_RUN; s++) run(s);
#pragma unroll
            for (int s = DN_RUN; s < 7 - DN_LAST; s++) load_w(s);
#pragma unroll
            for (int s = DN_RUN; s < 7 - DN_LAST; s++) run(s);
            if (DN_LAST) { load_w(6); run(6); }
            STAMP(8);
#pragma unroll
            for (int mt = 0; mt < 4; mt++) sts128f(sb + OFF_XS + 2048 * a + mt * 512 + lane * 16, dacc[mt]);
            named_sync(1, 128);
            uint4 q[4];
#pragma unroll
            for (int wq = 0; wq < 4; wq++) q[wq] = lds128(sb + OFF_XS + 2048 * wq + 16 * at);
            auto tagged = [&](uint32_t x0, uint32_t x1, uint32_t x2, uint32_t x3) {
                return (__float_as_uint((__uint_as_float(x0) + __uint_as_float(x1)) + (__uint_as_float(x2) + __uint_as_float(x3))) & ~3u) | ytag;
            };
            st_relaxed_128(py, tagged(q[0].x, q[1].x, q[2].x, q[3].x), tagged(q[0].y, q[1].y, q[2].y, q[3].y),
                           tagged(q[0].z, q[1].z, q[2].z, q[3].z), tagged(q[0].w, q[1].w, q[2].w, q[3].w));
        }
        STAMP(9);
        {
            const uint32_t key = __shfl_sync(0xffffffffu, mykey, 8 * a + 4 * (m >> 1));
            const uint32_t tok = 0xffffu - (key & 0xffffu);
            const float sg = bf_round(rcpf(1.f + ex2f(-L2E * bf_lo(unorder_key(key >> 16)))));
            const uint32_t xo = sb + OFF_X + 32 * (tok & ~63u) + 128 * (tok & 15u) + 2 * (tok & 48u) + ((2 * (lane & 15)) ^ ((tok & 1u) << 4));
            if (((tok >> 8) & 1) == h) {
                const uint32_t* yp = p.scr + S_Y + 1024 * cl + 32 * a + 4 * r + 2 * (m & 1) + (m >> 1);
                uint32_t pp[8], bad;
#pragma unroll 1
                do {
                    bad = 0;
#pragma unroll
                    for (int q = 0; q < 8; q++) pp[q] = ld_relaxed_32(yp + 128 * q);
#pragma unroll
                    for (int q = 0; q < 8; q++) bad |= pp[q] ^ ytag;
                } while (bad & 3u);
                const float y = ((__uint_as_float(pp[0]) + __uint_as_float(pp[1])) + (__uint_as_float(pp[2]) + __uint_as_float(pp[3]))) +
                                ((__uint_as_float(pp[4]) + __uint_as_float(pp[5])) + (__uint_as_float(pp[6]) + __uint_as_float(pp[7])));
                const uint32_t upd = pack_bf16(bf_round(y) * sg, 0.f);
                STAMP(11);
                mbar_wait(bar0 + 8 * B_ST, 0);
                uint32_t o;
                asm volatile("ld.shared.u16 %0, [%1];" : "=r"(o) : "r"(xo));
                asm volatile("st.global.u16 [%0], %1;" ::"l"(p.out + (size_t)tok * DM + 16 * cl + (lane & 15)), "r"(badd2(o, upd)) : "memory");
            }
            __syncwarp();
            if (elect_one()) mbar_arrive(bar0 + 8 * B_DONE);
        }
        STAMP(10); GSTAMP(15);
    } else {
        asm volatile("setmaxnreg.dec.sync.aligned.u32 %0;" ::"n"(FREG <= 136 ? 40 : 512 - 2 * NREG - FREG));
        const int q = warp - 12;
        sts32(sb + OFF_MISC + 16 + 4 * q, clk());
        const uint32_t t0 = __shfl_sync(0xffffffffu, lds32v(sb + OFF_MISC + 16 + 4 * q), 0);
        STAMP(0);
        if (q == 1) GSTAMP(14);
        const bool one = elect_one();
        const uint32_t rbar = bar0 + 8 * (B_ROW + q);
        if (one) {
            asm volatile("prefetch.tensormap [%0];" ::"l"(&maps.rows) : "memory");
            mbar_init(rbar, 1);
            if (q == 3) mbar_init(bar0 + 8 * B_WR, 1);
            fence_async();
            mbar_expect_tx(rbar, 8192);
            if (q == 3) {
                mbar_expect_tx(bar0 + 8 * B_WR, 2048);
                bulk_g2s(sb + OFF_GP, p.wr, 2048, bar0 + 8 * B_WR);
            }
        }
        __syncwarp();
        cluster_arrive();
        wait_until(t0 + ROW_DELAY + q * ROW_PERIOD);
        if (one) {
            tma_load_3d(sb + OFF_ROWS + 8192 * q, &maps.rows, 16 * b, 4 * q, rbar);
            asm volatile("prefetch.tensormap [%0];" ::"l"(&maps.u + q) : "memory");
        }
        __syncwarp();
        cluster_wait();
        cluster_arrive();
        STAMP(1);
        wait_until(t0 + X_DELAY + q * X_PERIOD);
        if (one) tma_load_4d_both(sb + OFF_X + 8192 * (4 * h + q), &maps.u, 16 * cl, 4 * (4 * h + q), bar0 + 8 * (B_X + 4 * h + q));
        STAMP(2);
        const char* src = (const char*)((b >> 6) ? p.wu : p.wg) + (64 * q + (b & 63)) * 7168 + 128 * lane;
        const uint32_t phase = t0 + PF_START + (b * PF_PERIOD >> 7) + q * PF_PERIOD;
        auto fill = [&](int j, uint32_t due, const CUtensorMap* map, int c0, int c3) {
            const uint32_t bar = bar0 + 8 * (B_FULL + q + 4 * (j & 1));
            wait_until(due);
            mbar_wait_bounded(bar + 8 * (B_EMPTY - B_FULL), (j >> 1) & 1);
            if (one) {
                mbar_expect_tx(bar, 8192);
                tma_load_4d(sb + OFF_RING + (q + 4 * (j & 1)) * 8192, map, c0, c3, bar);
            }
            STAMP(3 + (j >> 1));
        };
#pragma unroll 1
        for (int j = 0; j < 4; j++) {
            wait_until(phase + 4 * j * PF_PERIOD);
            asm volatile("prefetch.global.L2 [%0];" ::"l"(src) : "memory");
            if (lane < 24) asm volatile("prefetch.global.L2 [%0];" ::"l"(src + 4096) : "memory");
            src += 256 * 7168;
            STAMP(6);
            if (b < GU_CTAS) fill(j, t0 + LD_START + (b * PHG >> 7) + (q + 4 * j) * LD_PERIOD, &maps.wgu, 32 * b, q + 4 * j);
        }
#pragma unroll 1
        for (int j = 4; j < (q < 3 ? 6 : 5); j++)
            fill(j, phase + 4 * j * PF_PERIOD + (q + 4 * j - 16) * WD_EXTRA, &maps.wd, 64 * (b >> 3), 7 * (b & 7) + q + 4 * j - 16);
        if (q >= 2) mbar_wait_bounded(bar0 + 8 * (B_DONE - 2 + q), 0);
    }
    cluster_wait();
}

typedef CUresult (*EncodeFn)(CUtensorMap*, CUtensorMapDataType, cuuint32_t, void*, const cuuint64_t*, const cuuint64_t*,
                             const cuuint32_t*, const cuuint32_t*, CUtensorMapInterleave, CUtensorMapSwizzle,
                             CUtensorMapL2promotion, CUtensorMapFloatOOBfill);

void make_map(EncodeFn enc, CUtensorMap* m, int rank, const void* ptr, const cuuint64_t (&dims)[5], const cuuint64_t (&str)[4],
              const cuuint32_t (&box)[5], CUtensorMapSwizzle sw, CUtensorMapL2promotion pr) {
    const cuuint32_t es[5] = {1, 1, 1, 1, 1};
    CUresult rc = enc(m, CU_TENSOR_MAP_DATA_TYPE_BFLOAT16, rank, const_cast<void*>(ptr), dims, str, box, es, CU_TENSOR_MAP_INTERLEAVE_NONE, sw, pr,
                      CU_TENSOR_MAP_FLOAT_OOB_FILL_NONE);
    (void)rc;
}

}

extern "C" void kernel_launch(void* const* d_in, const int* in_sizes, int n_in, void* d_out, int out_size) {
    (void)in_sizes; (void)n_in; (void)out_size;
    static EncodeFn enc = nullptr;
    static void* scr = nullptr;
    if (!enc) {
        void* fn = nullptr;
        cudaDriverEntryPointQueryResult q;
        cudaGetDriverEntryPoint("cuTensorMapEncodeTiled", &fn, cudaEnableDefault, &q);
        enc = (EncodeFn)fn;
        cudaGetSymbolAddress(&scr, g_scr);
        cudaFuncSetAttribute(fused_kernel, cudaFuncAttributeMaxDynamicSharedMemorySize, SMEM_BYTES);
    }
    Maps maps;
    const uintptr_t ag = (uintptr_t)d_in[9], au = (uintptr_t)d_in[10];
    const auto noprom = CU_TENSOR_MAP_L2_PROMOTION_NONE, prom = CU_TENSOR_MAP_L2_PROMOTION_L2_128B;
    make_map(enc, &maps.rows, 3, d_in[0], {64, SEQ, 16, 1}, {2048, 128, 0}, {64, 16, 4, 1}, CU_TENSOR_MAP_SWIZZLE_128B, noprom);
    make_map(enc, &maps.u, 4, d_in[0], {DM, 4, 16, 32}, {32768, 2048, 131072}, {16, 4, 16, 4}, CU_TENSOR_MAP_SWIZZLE_32B, noprom);
    make_map(enc, &maps.out, 5, d_out, {DM, 4, 8, 2, 32}, {32768, 2048, 16384, 131072}, {16, 4, 2, 2, 4}, CU_TENSOR_MAP_SWIZZLE_NONE, noprom);
    make_map(enc, &maps.wgu, 4, (const void*)(ag < au ? ag : au), {FF, 64, 2, 16}, {FF * 2, ag < au ? au - ag : ag - au, 64 * FF * 2}, {32, 64, 2, 1},
             CU_TENSOR_MAP_SWIZZLE_64B, prom);
    make_map(enc, &maps.wd, 4, d_in[11], {DM, 64, 1, 56}, {2048, 131072, 131072}, {64, 64, 1, 1}, CU_TENSOR_MAP_SWIZZLE_128B, prom);
    Ptrs p;
    p.u = (const __nv_bfloat16*)d_in[0];
    p.logA = (const __nv_bfloat16*)d_in[1];
    p.Aim = (const __nv_bfloat16*)d_in[2];
    p.Cre = (const __nv_bfloat16*)d_in[3];
    p.Cim = (const __nv_bfloat16*)d_in[4];
    p.ldt = (const __nv_bfloat16*)d_in[5];
    p.dsk = (const __nv_bfloat16*)d_in[6];
    p.wr = (const __nv_bfloat16*)d_in[8];
    p.wg = (const __nv_bfloat16*)d_in[9];
    p.wu = (const __nv_bfloat16*)d_in[10];
    p.out = (__nv_bfloat16*)d_out;
    p.scr = (uint32_t*)scr;
    p.up_first = ag < au ? 0 : 4096;
    p.zero = 0;
    fused_kernel<<<NCTA + 2, NTHR, SMEM_BYTES, cudaStreamPerThread>>>(p, maps);
}
```

```cpp
#include <cuda_runtime.h>
#include <cuda_bf16.h>
#include <cuda_fp16.h>
#include <cuda.h>
#include <stdint.h>

namespace {

constexpr int SEQ = 2048, DM = 1024, NMODE = 128, FF = 3584;
constexpr int NCTA = 128, NTHR = 512;
constexpr int GU_CTAS = 112;

constexpr int OFF_X = 0;
constexpr int OFF_RING = 65536;
constexpr int ROW_PITCH = 2064;
constexpr int OFF_ROWS = OFF_RING + 32768;
constexpr int OFF_XS = OFF_RING + 65536;
constexpr int OFF_PRIV = OFF_XS + 8 * ROW_PITCH;
constexpr int PRIV = 8768;
constexpr int PLANE = 2240;
constexpr int OFF_GP = OFF_PRIV + 8 * PRIV;
constexpr int OFF_LC = OFF_GP + 8192;
constexpr int OFF_BAR = OFF_LC + 2048;
constexpr int OFF_MISC = OFF_BAR + 352;
constexpr int OFF_STAMP = OFF_MISC + 288;
constexpr int SMEM_BYTES = OFF_STAMP;

constexpr int B_X = 0, B_FULL = 8, B_EMPTY = 16, B_RECV = 24, B_XS = 28, B_DONE = 29, B_ST = 30, B_ROW = 32, B_WR = 36, B_KG = 37, B_VT = 38, B_PV = 39;

constexpr int T_DENSE = 4416;
constexpr int T_PATCH = T_DENSE + 2176;
constexpr int T_S4 = T_PATCH + 112;
constexpr int T_S8 = T_S4 + 736;
constexpr int REC = 272;

#define KG_UNROLL 4
constexpr int KGU = KG_UNROLL;
constexpr uint32_t SPIN_LIMIT = 1u << 22;
#define ROW_DELAY 300
#define H_SLEEP 0
#define NPRE 4
#define SEL_SLEEP 40
#define ROW_PERIOD 560
#define X_PERIOD 60
#define FINE 2
#define INC_AT 1
#define NREG 168
#define DN_RUN 6
#define FREG 144
#define NACC 1
#define LAST_DIRECT 0
#define DN_PRE 5
#define DN_LAST 1
#define GU_SPLIT 2
#define FIN_A 4
#define FIN_B 12
#define TORD 1
#define CW_EARLY 0
#define WAKE 63
#define LN_DUP 0
#define PHG 480
#define STAT_SLEEP 0
#define ST_GATE 3
#define XPROM 0
#define REPM 1
#define END_BAR 0
#define EARLY_DONE 1
#define MT_LAST 0
#define PAD 0
#define X_DELAY 2500
#define PF_START 3400
#define PF_PERIOD 525
#define WD_EXTRA 110
#define LD_LAG 520
#define LD_START 5300
#define LD_PERIOD ((PF_START + 16 * PF_PERIOD + LD_LAG - LD_START) / 15)

constexpr int S_STAT = 0;
constexpr int S_KEY = S_STAT + 8192;
constexpr int S_SEL = S_KEY + 2048;
constexpr int S_EPOCH = S_SEL + 128;
constexpr int S_H = S_EPOCH + 32;
constexpr int S_Y = S_H + 2 * GU_CTAS * 128;
constexpr int S_END = S_Y + 64 * 1024;
__device__ __align__(1024) uint32_t g_scr[S_END];

struct Ptrs {
    const __nv_bfloat16 *logA, *Aim, *Cre, *Cim, *ldt, *dsk, *u, *wr;
    uint32_t* scr;
    const __nv_bfloat16 *wg, *wu;
    __nv_bfloat16* out;
    uint32_t up_first;
    uint32_t zero;
};
struct Maps {
    CUtensorMap rows, u, out, wgu, wd;
};

__device__ __forceinline__ uint32_t clk() { uint32_t c; asm volatile("mov.u32 %0, %%clock;" : "=r"(c)); return c; }
#define STAMP(i) do { } while (0)
#define GSTAMP(i) do { } while (0)

template <int N> struct IC { static constexpr int value = N; };

__device__ __forceinline__ uint32_t s_u32(const void* p) { return (uint32_t)__cvta_generic_to_shared(p); }
__device__ __forceinline__ void mbar_init(uint32_t b, uint32_t n) {
    asm volatile("mbarrier.init.shared::cta.b64 [%0], %1;" ::"r"(b), "r"(n) : "memory");
}
__device__ __forceinline__ void mbar_expect_tx(uint32_t b, uint32_t bytes) {
    asm volatile("mbarrier.arrive.expect_tx.shared::cta.b64 _, [%0], %1;" ::"r"(b), "r"(bytes) : "memory");
}
__device__ __forceinline__ void mbar_arrive(uint32_t b) {
    asm volatile("mbarrier.arrive.shared::cta.b64 _, [%0];" ::"r"(b) : "memory");
}
__device__ __forceinline__ void mbar_arrive_peer(uint32_t b_cluster) {
    asm volatile("mbarrier.arrive.relaxed.cluster.shared::cluster.b64 _, [%0];" ::"r"(b_cluster) : "memory");
}
__device__ __forceinline__ void mbar_wait(uint32_t b, uint32_t parity) {
    asm volatile("{\n\t.reg .pred p;\nW:\n\tmbarrier.try_wait.parity.shared::cta.b64 p, [%0], %1;\n\t@!p bra W;\n\t}" ::"r"(b), "r"(parity) : "memory");
}
__device__ __forceinline__ void mbar_wait_bounded(uint32_t b, uint32_t parity) {
    asm volatile("{\n\t.reg .pred p;\n\t.reg .u32 c;\n\tmov.u32 c, 0;\n"
                 "W:\n\tmbarrier.try_wait.parity.shared::cta.b64 p, [%0], %1, 4000;\n\t@p bra D;\n\t"
                 "add.u32 c, c, 1;\n\tsetp.lt.u32 p, c, 1048576;\n\t@p bra W;\n\ttrap;\nD:\n\t}"
                 ::"r"(b), "r"(parity) : "memory");
}
__device__ __forceinline__ bool elect_one() {
    uint32_t p;
    asm volatile("{ .reg .pred P; elect.sync _|P, 0xffffffff; selp.u32 %0, 1, 0, P; }" : "=r"(p));
    return p != 0;
}
__device__ __forceinline__ uint32_t mapa(uint32_t a, uint32_t rank) {
    uint32_t r;
    asm("mapa.shared::cluster.u32 %0, %1, %2;" : "=r"(r) : "r"(a), "r"(rank));
    return r;
}
__device__ __forceinline__ void cluster_arrive() { asm volatile("barrier.cluster.arrive.relaxed.aligned;" ::: "memory"); }
__device__ __forceinline__ void cluster_wait() { asm volatile("barrier.cluster.wait.aligned;" ::: "memory"); }
__device__ __forceinline__ void tma_load_3d(uint32_t dst, const CUtensorMap* m, int c1, int c2, uint32_t bar) {
    asm volatile("cp.async.bulk.tensor.3d.shared::cluster.global.mbarrier::complete_tx::bytes [%0], [%1, {%3, %4, %5}], [%2];"
                 ::"r"(dst), "l"(m), "r"(bar), "r"(0), "r"(c1), "r"(c2) : "memory");
}
__device__ __forceinline__ void tma_load_4d(uint32_t dst, const CUtensorMap* m, int c0, int c3, uint32_t bar) {
    uint64_t pol;
    asm("createpolicy.fractional.L2::evict_first.b64 %0, 1.0;" : "=l"(pol));
    asm volatile("cp.async.bulk.tensor.4d.shared::cluster.global.mbarrier::complete_tx::bytes.L2::cache_hint [%0], [%1, {%3, %5, %5, %4}], [%2], %6;"
                 ::"r"(dst), "l"(m), "r"(bar), "r"(c0), "r"(c3), "r"(0), "l"(pol) : "memory");
}
__device__ __forceinline__ void wait_until(uint32_t t) {
    asm volatile("{\n\t.reg .pred p;\n\t.reg .s32 c;\nW:\n\tmov.u32 c, %%clock;\n\tsub.s32 c, %0, c;\n\tshr.s32 c, c, 2;\n\tsetp.gt.s32 p, c, %1;\n\t"
                 "@p nanosleep.u32 c;\n\t@p bra.uni W;\n\t}" ::"r"(t), "n"(WAKE) : "memory");
}
__device__ __forceinline__ void tma_load_4d_both(uint32_t dst, const CUtensorMap* m, int c0, int c3, uint32_t bar) {
    asm volatile("cp.async.bulk.tensor.4d.shared::cluster.global.mbarrier::complete_tx::bytes.multicast::cluster [%0], [%1, {%3, %6, %6, %4}], [%2], %5;"
                 ::"r"(dst), "l"(m), "r"(bar), "r"(c0), "r"(c3), "h"((uint16_t)3), "r"(0) : "memory");
}
__device__ __forceinline__ void bulk_g2s(uint32_t dst, const void* src, uint32_t bytes, uint32_t bar) {
    asm volatile("cp.async.bulk.shared::cluster.global.mbarrier::complete_tx::bytes [%0], [%1], %2, [%3];"
                 ::"r"(dst), "l"(src), "r"(bytes), "r"(bar) : "memory");
}
__device__ __forceinline__ void fence_async() { asm volatile("fence.proxy.async.shared::cta;" ::: "memory"); }
__device__ __forceinline__ void named_sync(int id, int n) { asm volatile("bar.sync %0, %1;" ::"r"(id), "r"(n) : "memory"); }

__device__ __forceinline__ void ldsm4(uint32_t* r, uint32_t a) {
    asm volatile("ldmatrix.sync.aligned.m8n8.x4.shared.b16 {%0,%1,%2,%3}, [%4];"
                 : "=r"(r[0]), "=r"(r[1]), "=r"(r[2]), "=r"(r[3]) : "r"(a));
}
__device__ __forceinline__ void ldsm4t(uint32_t* r, uint32_t a) {
    asm volatile("ldmatrix.sync.aligned.m8n8.x4.trans.shared.b16 {%0,%1,%2,%3}, [%4];"
                 : "=r"(r[0]), "=r"(r[1]), "=r"(r[2]), "=r"(r[3]) : "r"(a));
}
__device__ __forceinline__ void stsm4t(uint32_t a, const uint32_t* r) {
    asm volatile("stmatrix.sync.aligned.m8n8.x4.trans.shared.b16 [%0], {%1,%2,%3,%4};"
                 ::"r"(a), "r"(r[0]), "r"(r[1]), "r"(r[2]), "r"(r[3]) : "memory");
}
__device__ __forceinline__ uint32_t lds32(uint32_t a) { uint32_t v; asm volatile("ld.shared.u32 %0, [%1];" : "=r"(v) : "r"(a)); return v; }
__device__ __forceinline__ uint32_t lds32v(uint32_t a) { uint32_t v; asm volatile("ld.volatile.shared.u32 %0, [%1];" : "=r"(v) : "r"(a)); return v; }
__device__ __forceinline__ uint2 lds64(uint32_t a) { uint2 v; asm volatile("ld.shared.v2.u32 {%0,%1}, [%2];" : "=r"(v.x), "=r"(v.y) : "r"(a)); return v; }
__device__ __forceinline__ uint4 lds128(uint32_t a) {
    uint4 v; asm volatile("ld.shared.v4.u32 {%0,%1,%2,%3}, [%4];" : "=r"(v.x), "=r"(v.y), "=r"(v.z), "=r"(v.w) : "r"(a)); return v;
}
template <int D> __device__ __forceinline__ void sts16x2(uint32_t a, float x) {
    asm volatile("{ .reg .b16 h; cvt.rn.bf16.f32 h, %1; st.shared.b16 [%0], h; st.shared.b16 [%0 + %2], h; }" ::"r"(a), "f"(x), "n"(D) : "memory");
}
__device__ __forceinline__ void sts32(uint32_t a, uint32_t v) { asm volatile("st.shared.u32 [%0], %1;" ::"r"(a), "r"(v) : "memory"); }
__device__ __forceinline__ void sts64(uint32_t a, uint32_t x, uint32_t y) { asm volatile("st.shared.v2.u32 [%0], {%1,%2};" ::"r"(a), "r"(x), "r"(y) : "memory"); }
__device__ __forceinline__ void sts128(uint32_t a, uint32_t x, uint32_t y, uint32_t z, uint32_t w) {
    asm volatile("st.shared.v4.u32 [%0], {%1,%2,%3,%4};" ::"r"(a), "r"(x), "r"(y), "r"(z), "r"(w) : "memory");
}
__device__ __forceinline__ void sts128f(uint32_t a, const float* c) {
    asm volatile("st.shared.v4.f32 [%0], {%1,%2,%3,%4};" ::"r"(a), "f"(c[0]), "f"(c[1]), "f"(c[2]), "f"(c[3]) : "memory");
}
__device__ __forceinline__ uint2 ldg64(const void* p) {
    uint2 v; asm volatile("ld.global.nc.L1::no_allocate.v2.u32 {%0,%1}, [%2];" : "=r"(v.x), "=r"(v.y) : "l"(p)); return v;
}
__device__ __forceinline__ uint32_t ldg16(const void* p) {
    uint16_t v; asm volatile("ld.global.nc.u16 %0, [%1];" : "=h"(v) : "l"(p)); return v;
}
__device__ __forceinline__ uint32_t ld_relaxed_32(const void* p) {
    uint32_t v; asm volatile("ld.relaxed.gpu.global.u32 %0, [%1];" : "=r"(v) : "l"(p) : "memory"); return v;
}
__device__ __forceinline__ uint2 ld_relaxed_64(const void* p) {
    unsigned long long v;
    asm volatile("ld.relaxed.gpu.global.u64 %0, [%1];" : "=l"(v) : "l"(p) : "memory");
    return make_uint2((uint32_t)v, (uint32_t)(v >> 32));
}
__device__ __forceinline__ uint4 ld_relaxed_128(const void* p) {
    uint4 v; asm volatile("ld.relaxed.gpu.global.v4.u32 {%0,%1,%2,%3}, [%4];" : "=r"(v.x), "=r"(v.y), "=r"(v.z), "=r"(v.w) : "l"(p) : "memory"); return v;
}
__device__ __forceinline__ void st_relaxed_32(void* p, uint32_t v) {
    asm volatile("st.relaxed.gpu.global.u32 [%0], %1;" ::"l"(p), "r"(v) : "memory");
}
__device__ __forceinline__ void st_relaxed_128(void* p, uint32_t x, uint32_t y, uint32_t z, uint32_t w) {
    asm volatile("st.relaxed.gpu.global.v4.u32 [%0], {%1,%2,%3,%4};" ::"l"(p), "r"(x), "r"(y), "r"(z), "r"(w) : "memory");
}
__device__ __forceinline__ void st_relaxed_64(void* p, uint32_t x, uint32_t y) {
    asm volatile("st.relaxed.gpu.global.u64 [%0], %1;" ::"l"(p), "l"((unsigned long long)x | ((unsigned long long)y << 32)) : "memory");
}
__device__ __forceinline__ void mma_bf16(float* c, uint32_t a0, uint32_t a1, uint32_t a2, uint32_t a3, uint32_t b0, uint32_t b1) {
    asm("mma.sync.aligned.m16n8k16.row.col.f32.bf16.bf16.f32 {%0,%1,%2,%3}, {%4,%5,%6,%7}, {%8,%9}, {%0,%1,%2,%3};"
                 : "+f"(c[0]), "+f"(c[1]), "+f"(c[2]), "+f"(c[3]) : "r"(a0), "r"(a1), "r"(a2), "r"(a3), "r"(b0), "r"(b1));
}
__device__ __forceinline__ void mma_bf16v(float* c, const uint32_t* a, uint32_t b0, uint32_t b1) {
    asm volatile("mma.sync.aligned.m16n8k16.row.col.f32.bf16.bf16.f32 {%0,%1,%2,%3}, {%4,%5,%6,%7}, {%8,%9}, {%0,%1,%2,%3};"
                 : "+f"(c[0]), "+f"(c[1]), "+f"(c[2]), "+f"(c[3]) : "r"(a[0]), "r"(a[1]), "r"(a[2]), "r"(a[3]), "r"(b0), "r"(b1));
}
__device__ __forceinline__ void mma_bf16_z(float* c, uint32_t a0, uint32_t a1, uint32_t a2, uint32_t a3, uint32_t b0, uint32_t b1) {
    asm("mma.sync.aligned.m16n8k16.row.col.f32.bf16.bf16.f32 {%0,%1,%2,%3}, {%4,%5,%6,%7}, {%8,%9}, {%10,%10,%10,%10};"
        : "=f"(c[0]), "=f"(c[1]), "=f"(c[2]), "=f"(c[3]) : "r"(a0), "r"(a1), "r"(a2), "r"(a3), "r"(b0), "r"(b1), "f"(0.f));
}
__device__ __forceinline__ void mma_f16(float* c, const uint4& a, uint32_t b0, uint32_t b1) {
    asm("mma.sync.aligned.m16n8k16.row.col.f32.f16.f16.f32 {%0,%1,%2,%3}, {%4,%5,%6,%7}, {%8,%9}, {%0,%1,%2,%3};"
                 : "+f"(c[0]), "+f"(c[1]), "+f"(c[2]), "+f"(c[3]) : "r"(a.x), "r"(a.y), "r"(a.z), "r"(a.w), "r"(b0), "r"(b1));
}
__device__ __forceinline__ uint32_t pack_bf16(float lo, float hi) {
    uint32_t r; asm("cvt.rn.bf16x2.f32 %0, %1, %2;" : "=r"(r) : "f"(hi), "f"(lo)); return r;
}
__device__ __forceinline__ uint32_t pack_bf16v(float lo, float hi) {
    uint32_t r; asm("cvt.rn.satfinite.bf16x2.f32 %0, %1, %2;" : "=r"(r) : "f"(hi), "f"(lo)); return r;
}
__device__ __forceinline__ uint32_t pack_f16(float lo, float hi) {
    uint32_t r; asm("cvt.rn.f16x2.f32 %0, %1, %2;" : "=r"(r) : "f"(hi), "f"(lo)); return r;
}
__device__ __forceinline__ float bf_lo(uint32_t v) { return __uint_as_float(v << 16); }
__device__ __forceinline__ float bf_hi(uint32_t v) { return __uint_as_float(v & 0xffff0000u); }
__device__ __forceinline__ float bf_round(float x) { return __uint_as_float(pack_bf16(0.f, x)); }
__device__ __forceinline__ __nv_bfloat162 as_b2(uint32_t x) { return *reinterpret_cast<__nv_bfloat162*>(&x); }
__device__ __forceinline__ uint32_t as_u(__nv_bfloat162 x) { return *reinterpret_cast<uint32_t*>(&x); }
__device__ __forceinline__ uint32_t badd2(uint32_t a, uint32_t b) { uint32_t r; asm("add.rn.bf16x2 %0, %1, %2;" : "=r"(r) : "r"(a), "r"(b)); return r; }
__device__ __forceinline__ float rcpf(float x) { float r; asm("rcp.approx.ftz.f32 %0, %1;" : "=f"(r) : "f"(x)); return r; }
__device__ __forceinline__ float sqrtaf(float x) { float r; asm("sqrt.approx.ftz.f32 %0, %1;" : "=f"(r) : "f"(x)); return r; }
__device__ __forceinline__ float ex2f(float x) { float r; asm("ex2.approx.ftz.f32 %0, %1;" : "=f"(r) : "f"(x)); return r; }
constexpr float L2E = 1.4426950408889634f;
constexpr uint32_t ONES = 0x3f803f80u;

__device__ __forceinline__ uint2 recip2(uint32_t s2) {
    const uint32_t hi = pack_bf16(rcpf(bf_lo(s2)), rcpf(bf_hi(s2)));
    return make_uint2(hi, as_u(__hmul2(__hfma2(__hneg2(as_b2(s2)), as_b2(hi), as_b2(ONES)), as_b2(hi))));
}
__device__ __forceinline__ uint32_t normalize2(uint32_t x, __nv_bfloat162 m, __nv_bfloat162 rh, __nv_bfloat162 rl) {
    const __nv_bfloat162 d = __hsub2(as_b2(x), m);
    return as_u(__hfma2(d, rh, __hmul2(d, rl)));
}

__device__ __forceinline__ uint32_t unorder_key(uint32_t k16) { return k16 ^ ((k16 & 0x8000u) ? 0x8000u : 0xffffu); }

struct cplx { float r, i; };
__device__ __forceinline__ cplx csq(cplx a) { return {a.r * a.r - a.i * a.i, (a.r + a.r) * a.i}; }
__device__ __forceinline__ cplx csq_conj(cplx a) { return {a.r * a.r - a.i * a.i, (-a.r - a.r) * a.i}; }
__device__ __forceinline__ cplx cexpp(float a2, float th) {
    float m = ex2f(a2), s, c;
    __sincosf(th, &s, &c);
    return {m * c, m * s};
}
struct hc { __half2 r, i; };
__device__ __forceinline__ __half2 as_h2(uint32_t x) { return *reinterpret_cast<__half2*>(&x); }
__device__ __forceinline__ uint32_t as_u(__half2 x) { return *reinterpret_cast<uint32_t*>(&x); }
__device__ __forceinline__ hc hmul(hc a, hc b) {
    return {__hfma2(a.r, b.r, __hneg2(__hmul2(a.i, b.i))), __hfma2(a.r, b.i, __hmul2(a.i, b.r))};
}
__device__ __forceinline__ hc hpack(cplx a, cplx b) { return {as_h2(pack_f16(a.r, b.r)), as_h2(pack_f16(a.i, b.i))}; }
__device__ __forceinline__ void st_pair(uint32_t a, hc x, hc y) { sts128(a, as_u(x.r), as_u(x.i), as_u(y.r), as_u(y.i)); }
__device__ __forceinline__ void st_quad(uint32_t a, hc x, hc y) { sts128(a, as_u(x.r), as_u(y.r), as_u(x.i), as_u(y.i)); }

#define KSTAMP(i, dep) do { } while (0)
__device__ __forceinline__ void kgen_mma(float (&acc)[5][4], uint32_t priv, int lane, uint2 la, uint2 aim, uint2 cre, uint2 cim, float dt, uint32_t cs2) {
    const int g = lane >> 2, t = lane & 3;
#pragma unroll
    for (int i = 0; i < 5; i++) { acc[i][0] = acc[i][1] = acc[i][2] = acc[i][3] = 0.f; }
    const uint32_t wr = priv + lane * REC, rd = priv + 2 * t * REC;
    const float ndl = -dt * L2E;
#pragma unroll 1
    for (int ps = 0; ps < 2; ps++) {
        const uint32_t lw = ps ? la.y : la.x, iw = ps ? aim.y : aim.x;
        const uint32_t crw = as_u(__hmul2(as_b2(ps ? cre.y : cre.x), as_b2(cs2))), ciw = as_u(__hmul2(as_b2(ps ? cim.y : cim.x), as_b2(cs2)));
        const uint32_t ap = pack_bf16(ex2f(bf_lo(lw) * L2E), ex2f(bf_hi(lw) * L2E));
        const float a2[2] = {bf_lo(ap) * ndl, bf_hi(ap) * ndl}, th[2] = {bf_lo(iw) * dt, bf_hi(iw) * dt};
        cplx p1[2], p2[2], p4[2], p8[2], p32[2], p64[2], p128[2], p256[2], p512[2];
#pragma unroll
        for (int i = 0; i < 2; i++) {
            p1[i] = cexpp(a2[i], th[i]); p32[i] = cexpp(a2[i] * 32.f, th[i] * -32.f);
            p2[i] = csq(p1[i]); p4[i] = csq(p2[i]); p8[i] = csq_conj(p4[i]);
            p64[i] = csq(p32[i]); p128[i] = csq_conj(p64[i]); p256[i] = csq(p128[i]); p512[i] = csq(p256[i]);
        }
        const hc C = {as_h2(pack_f16(bf_lo(crw), bf_hi(crw))), as_h2(pack_f16(bf_lo(ciw), bf_hi(ciw)))};
        const hc z1 = hpack(p1[0], p1[1]), z2 = hpack(p2[0], p2[1]), z4 = hpack(p4[0], p4[1]);
        const hc y8 = hpack(p8[0], p8[1]), y32 = hpack(p32[0], p32[1]), y64 = hpack(p64[0], p64[1]);
        const hc z128 = hpack(p128[0], p128[1]), z256 = hpack(p256[0], p256[1]), z512 = hpack(p512[0], p512[1]);
        KSTAMP(8 + 3 * ps, z512.r);
        __syncwarp();
        const hc c1 = hmul(C, z1), c2 = hmul(C, z2), c5 = hmul(c1, z4), c6 = hmul(c2, z4);
        st_pair(wr + 160, hmul(c1, z128), hmul(c2, z128));
        st_pair(wr + 128, c1, c2);
        st_pair(wr + 176, hmul(c5, z128), hmul(c6, z128));
        st_pair(wr + 144, c5, c6);
        const hc y16 = hmul(y8, y8), y48 = hmul(y16, y32), y24 = hmul(y16, y8), y40 = hmul(y32, y8), y56 = hmul(y48, y8), y72 = hmul(y64, y8);
        st_quad(wr, {as_h2(0x3c003c00u), as_h2(0u)}, y8);
        st_quad(wr + 80, hmul(y64, y16), hmul(y64, y24));
        st_quad(wr + 16, y16, y24);
        st_quad(wr + 96, hmul(y64, y32), hmul(y64, y40));
        st_quad(wr + 32, y32, y40);
        st_quad(wr + 112, hmul(y64, y48), hmul(y64, y56));
        st_quad(wr + 48, y48, y56);
        st_quad(wr + 64, y64, y72);
        const hc z258 = hmul(z256, z2);
        st_pair(wr + 192, hmul(z256, z1), z258);
        st_pair(wr + 224, z2, hmul(z512, z4));
        st_pair(wr + 240, z2, hmul(z512, z512));
        st_pair(wr + 208, z258, z512);
        KSTAMP(9 + 3 * ps, z512.r);
        __syncwarp();
#pragma unroll KGU
        for (int k2 = 0; k2 < 4; k2++) {
#pragma unroll
            for (int s = 0; s < 2; s++) {
                const uint32_t o = rd + k2 * 8 * REC + s * REC;
                const uint4 A = lds128(o + 16 * g);
                const uint2 h = lds64(o + 128 + 8 * g);
                const uint4 M = lds128(o + 192 + 16 * (g & 1)), N = lds128(o + 224 + 8 * (g & 2));
                const hc H0 = {as_h2(h.x), as_h2(h.y)};
                const hc H1 = hmul(H0, {as_h2(N.x), as_h2(N.y)}), H2 = hmul(H0, {as_h2(M.x), as_h2(M.y)});
                const hc H3 = hmul(H2, {as_h2(M.z), as_h2(M.w)}), H4 = hmul(H3, {as_h2(N.z), as_h2(N.w)});
                mma_f16(acc[0], A, h.x, h.y);
                mma_f16(acc[1], A, as_u(H1.r), as_u(H1.i));
                mma_f16(acc[2], A, as_u(H2.r), as_u(H2.i));
                mma_f16(acc[3], A, as_u(H3.r), as_u(H3.i));
                mma_f16(acc[4], A, as_u(H4.r), as_u(H4.i));
            }
        }
        KSTAMP(10 + 3 * ps, z512.r);
    }
}

__device__ __forceinline__ void kgen_tables(const float (&acc)[5][4], uint32_t priv, int lane, float scale, float k0) {
    const int g = lane >> 2, t0 = lane & 1, t1 = (lane >> 1) & 1;
    __syncwarp();
    sts128(priv + 16 * lane + (lane < 17 ? T_PATCH - 48 : T_S4 + 608 - 272), 0, 0, 0, 0);
    if (lane < 20) sts128(priv + 16 * lane + (lane < 8 ? 0 : lane < 16 ? PLANE - 128 : T_DENSE - 256), 0, 0, 0, 0);
    uint32_t w2[2], w3[2], w4[2], ab[2], W[2], pv[2];
#pragma unroll
    for (int hf = 0; hf < 2; hf++) {
        const float k1 = acc[0][2 * hf] * scale, k2 = acc[0][2 * hf + 1] * scale, k3 = acc[1][2 * hf] * scale, k4 = acc[1][2 * hf + 1] * scale;
        w2[hf] = pack_bf16(k2, k1); w3[hf] = pack_bf16(k3, k2); w4[hf] = pack_bf16(k4, k3);
        ab[hf] = pack_bf16(acc[2][2 * hf + 1] * scale, acc[2][2 * hf] * scale);
        W[hf] = __byte_perm(w4[hf], ab[hf], 0x5410);
    }
    pv[1] = __shfl_xor_sync(0xffffffffu, t0 ? W[0] : W[1], 1);
    pv[0] = __shfl_sync(0xffffffffu, t0 ? W[1] : W[0], t0 ? lane - 1 : lane < 4 ? 31 - lane : lane - 3);
    const uint32_t kk = pack_bf16(k0, 0.f);
    if (lane == 0) pv[0] = __byte_perm(kk, pv[0], 0x5410);
    const uint32_t pd = priv + T_DENSE + 64 + 512 * t1 + 64 * g + 16 * t0;
#pragma unroll
    for (int hf = 0; hf < 2; hf++) {
        sts128(pd + 32 * hf, __byte_perm(w2[hf], pv[hf], 0x5432), w2[hf], w3[hf], w4[hf]);
        sts128(pd + 32 * hf + 1024, __byte_perm(pv[hf], 0, 0x3232), __byte_perm(ab[hf], pv[hf], 0x7632), ab[hf], __byte_perm(ab[hf], 0, 0x1010));
    }
    __syncwarp();
    if (lane == 31) {
        const uint32_t aa = __byte_perm(ab[1], 0, 0x1010);
        sts32(priv + T_DENSE + 60, kk);
        sts128(priv + T_PATCH - 64, aa, aa, aa << 16, 0u);
    }
}
__device__ __forceinline__ void kgen_tables2(const float (&acc)[5][4], uint32_t priv, int lane, float scale) {
    const int g = lane >> 2, t0 = lane & 1, t1 = (lane >> 1) & 1;
    const uint32_t p4 = priv + T_S4 + 16 * (6 + g + 8 * t1) + 4 * (t0 ^ 1), p8 = priv + T_S8 + 8 * (6 + g + 8 * t1 + 32 * t0);
#pragma unroll
    for (int i = 0; i < 4; i++) {
        sts16x2<18>(p4 + 256 * (i & 1) + 8 * (i >> 1), acc[3][i] * scale);
        sts16x2<10>(p8 + 128 * (i & 1) + 4 * (i >> 1), acc[4][i] * scale);
    }
    if (lane == 31) {
        const uint32_t c3 = pack_bf16(acc[3][3] * scale, 0.f);
        sts128(priv + T_PATCH + 48, c3, c3 * 0x10001u, c3 << 16, 0u);
    }
    __syncwarp();
}

__device__ __forceinline__ void ld_frag(uint32_t (&T)[4], uint32_t q) { T[0] = lds32(q); T[1] = lds32(q + 32); T[2] = lds32(q - 32); T[3] = lds32v(q); }
__device__ __forceinline__ void ld_swap(uint32_t (&T)[4], uint32_t q) { T[2] = lds32v(q); T[3] = lds32v(q + 32); T[0] = lds32v(q - 32); T[1] = lds32v(q); }
__device__ __forceinline__ void add_frag(uint32_t (&S)[4], const uint32_t (&E)[4], const uint32_t (&O)[4]) {
    S[0] = badd2(E[0], O[1]); S[1] = badd2(E[1], O[3]); S[2] = badd2(E[2], O[0]); S[3] = badd2(E[3], O[2]);
}
__device__ __forceinline__ void mma4(float* c, const uint32_t (&a)[4], uint32_t b0, uint32_t b1, bool first = false) {
    if (first) mma_bf16_z(c, a[0], a[1], a[2], a[3], b0, b1);
    else mma_bf16(c, a[0], a[1], a[2], a[3], b0, b1);
}
template <bool FIRST>
__device__ __forceinline__ void dense_step(float (&acc)[16][4], float (&B)[8][4], uint32_t (&T0)[4], uint32_t (&T1)[4], uint32_t (&R)[8][4],
                                           uint32_t pq, uint32_t va) {
    uint32_t T2[4], T3[4], S[4], s[8][2];
#pragma unroll
    for (int i = NPRE; i < 8; i++) ldsm4(R[i], va + i * 256);
    ld_frag(T2, pq + 1024); ld_swap(T3, pq + 1536);
    add_frag(S, T0, T1);
#pragma unroll
    for (int i = 0; i < 8; i++) {
        s[i][0] = badd2(R[i][0], R[i][3]); s[i][1] = badd2(R[i][1], R[i][2]);
        mma4(acc[2 * i], T0, R[i][0], R[i][1], FIRST);
        mma4(B[i], T1, R[i][2], R[i][3], FIRST);
        mma4(acc[2 * i + 1], S, s[i][0], s[i][1], FIRST);
    }
    ld_frag(T0, pq - 64); ld_swap(T1, pq + 448);
    add_frag(S, T2, T3);
#pragma unroll
    for (int i = 0; i < 7; i++) {
        if (!FIRST || i) mma4(acc[2 * i + 2], T2, R[i][0], R[i][1]);
        mma4(B[i + 1], T3, R[i][2], R[i][3]);
        mma4(acc[2 * i + 3], S, s[i][0], s[i][1]);
        if (i < NPRE) ldsm4(R[i], va + 16 + i * 256);
    }
}
template <class Wait, class After>
__device__ __forceinline__ void dense_phase(float (&acc)[16][4], uint32_t priv, int lane, Wait wait_for_tokens, After after_loop) {
    const int m = lane >> 3, r = lane & 7;
    const uint32_t pb = priv + T_DENSE + 4 * (15 + (lane >> 2) - 2 * (lane & 3));
    const uint32_t v8 = priv + 128 * (m >> 1) + 16 * r;
    float B[8][4];
    uint32_t T0[4], T1[4], R[8][4];
    uint32_t pq = pb + 512, va = v8 + PLANE * ((m ^ (m >> 1)) & 1);
    ld_frag(T0, pq); ld_swap(T1, pq + 512);
    wait_for_tokens();
#pragma unroll
    for (int i = 0; i < NPRE; i++) ldsm4(R[i], va + i * 256);
    dense_step<true>(acc, B, T0, T1, R, pq, va);
#pragma unroll 1
    do {
        pq -= 64; va += 16;
        dense_step<false>(acc, B, T0, T1, R, pq, va);
    } while (pq != pb + 64);
    after_loop();
    KSTAMP(14, as_h2(0u));
    const uint32_t pp = pb + T_PATCH - T_DENSE - 24;
    uint32_t N0[4], N1[4];
    ld_swap(T1, pb); ld_frag(N0, pp); ld_swap(N1, pp);
#pragma unroll
    for (int i = NPRE; i < 8; i++) ldsm4(R[i], va + 16 + i * 256);
#pragma unroll
    for (int i = 0; i < 8; i++)
#pragma unroll
        for (int j = 0; j < 4; j++) {
            acc[2 * i + 1][j] = (acc[2 * i + 1][j] - acc[2 * i][j]) - B[i][j];
            if (i) acc[2 * i][j] += B[i - 1][j];
        }
#pragma unroll
    for (int i = 0; i < 8; i++) {
        mma4(acc[2 * i], T0, R[i][0], R[i][1]);
        mma4(acc[2 * i + 1], T1, R[i][2], R[i][3]);
        if (i >= 4) {
            mma4(acc[2 * i], N0, R[i - 4][0], R[i - 4][1]);
            mma4(acc[2 * i + 1], N1, R[i - 4][2], R[i - 4][3]);
        }
    }
    const uint32_t b = v8 + PLANE + 112;
    const uint32_t bz = (m & 1) ? priv : b, bm = (m & 1) ? b : b + 512;
    const uint32_t M[4] = {lds32(pb + 4 * 520), lds32(pb + 4 * 528), lds32v(pp + 32), lds32(pp + 64)};
#pragma unroll
    for (int i = 0; i < 6; i++) {
        uint32_t V[4];
        ldsm4(V, i < 2 ? bz + ((m & 1) ? 0 : i * 256) : bm + (i - 2) * 256);
        mma4(acc[2 * i + 4], M, V[0], V[1]);
        mma4(acc[2 * i + 5], M, V[2], V[3]);
    }
}

__device__ __forceinline__ uint32_t ones2(int c, int lo, int n) {
    return (((uint32_t)(c - lo) < (uint32_t)n) ? 0x3f80u : 0u) | (((uint32_t)(c + 1 - lo) < (uint32_t)n) ? 0x3f800000u : 0u);
}
template <int L1, int N1, int L2, int N2, int D>
__device__ __forceinline__ void box_ones(uint32_t dst, int d) { sts128(dst, ones2(d, L1, N1), ones2(d, L2, N2), ones2(d + D, L1, N1), ones2(d + D, L2, N2)); }
__device__ __forceinline__ uint32_t tok_at(int T) { return PLANE * ((T >> 3) & 1) + 16 * ((T >> 4) + 8) + 2 * (T & 7); }
__device__ __forceinline__ float left_col(float cur, float prev, int lane) {
    return __shfl_sync(0xffffffffu, (lane & 3) == 3 ? prev : cur, lane + 3, 4);
}
struct Tails {
    uint4 q4, q8, B4[5], ad;
    uint2 B8[8];
    uint32_t W[2][4], A[2][2][4];
    float p1, p3, p8;
    static __host__ __device__ constexpr bool is8(int k) { return k >= 4 && (TORD ? (k & 1) : (k & 4) == 0); }
    static __host__ __device__ constexpr int grp(int k) { return k < 4 ? k : TORD ? (k - 4) / 2 + (is8(k) ? 0 : 4) : (k & 3) + 4 * ((k - 4) >> 3) + (is8(k) ? 0 : 4); }
    __device__ __forceinline__ void load(int k, uint32_t priv) {
        uint32_t* w = W[k & 1];
        const uint32_t o = priv + 128 * grp(k);
        if (is8(k)) {
            const uint2 vy = lds64(o + ad.w), vx = lds64(o + ad.z);
            w[0] = vy.x; w[1] = vy.y; w[2] = vx.x; w[3] = vx.y;
        } else { w[0] = lds32(o + ad.y); w[1] = lds32(o + ad.x + 16); w[2] = lds32(o + ad.x); w[3] = lds32v(o + ad.y); }
    }
    __device__ __forceinline__ void box(int k, int lane) {
        const uint32_t* w = W[k & 1];
        const uint4 q = is8(k) ? q8 : q4;
        uint32_t (&a)[2][4] = A[k & 1];
        float X[4], Y[4];
        mma_bf16_z(Y, q.x, q.y, q.z, q.w, w[0], w[1]);
        mma_bf16_z(X, q.x, q.y, q.z, q.w, w[2], w[3]);
        a[0][0] = pack_bf16(X[0], X[1]); a[0][1] = pack_bf16(Y[0], Y[1]);
        if (is8(k)) {
            a[0][2] = pack_bf16(left_col(Y[3], p8, lane), Y[2]); a[0][3] = pack_bf16(X[2], X[3]);
            p8 = Y[3];
        } else {
            a[0][2] = pack_bf16(X[2], X[3]); a[0][3] = pack_bf16(Y[2], Y[3]);
            a[1][0] = pack_bf16(left_col(Y[1], p1, lane), Y[0]); a[1][1] = pack_bf16v(X[0], X[1]);
            a[1][2] = pack_bf16(left_col(Y[3], p3, lane), Y[2]); a[1][3] = pack_bf16v(X[2], X[3]);
            p1 = Y[1]; p3 = Y[3];
        }
    }
    __device__ __forceinline__ void taps(int k, float (&acc)[16][4]) {
        const int G = grp(k);
        if (is8(k)) {
#pragma unroll
            for (int b = 0; b < 8; b++) if (G + 8 + b < 16) mma4(acc[G + 8 + b], A[k & 1][0], B8[b].x, B8[b].y);
        } else {
#pragma unroll
            for (int b = 0; b < 5; b++) if (G + 4 + b < 16) mma4(acc[G + 4 + b], A[k & 1][0], B4[b].x, B4[b].y);
#pragma unroll
            for (int b = 0; b < 5; b++) if (G + 4 + b < 16) mma4(acc[G + 4 + b], A[k & 1][1], B4[b].z, B4[b].w);
        }
    }
    __device__ __forceinline__ void start(uint32_t lc, uint32_t priv, uint32_t tap, int lane) {
        ad = lds128(lc + 1024); q4 = lds128(lc); q8 = lds128(lc + 512);
        p1 = p3 = p8 = 0.f;
        load(0, priv); load(1, priv);
#pragma unroll
        for (int i = 0; i < 5; i++) B4[i] = lds128(priv + T_S4 + 128 * i + 2 * tap);
        box(0, lane);
    }
    template <int K0, int K1>
    __device__ __forceinline__ void run(float (&acc)[16][4], uint32_t priv, uint32_t tap, int lane) {
#pragma unroll
        for (int k = K0; k < K1; k++) {
            if (k + 2 < 20) load(k + 2, priv);
            if (k == 4) {
#pragma unroll
                for (int i = 0; i < 8; i++) B8[i] = lds64(priv + T_S8 + 64 * i + tap);
            }
            if (k + 1 < 20) box(k + 1, lane);
            taps(k, acc);
        }
    }
};
__device__ __forceinline__ void lane_consts(uint32_t dst, int unit, int lane) {
    const int g = lane >> 2, t = lane & 3, m = lane >> 3, r = lane & 7;
    if (unit == 0) box_ones<0, 5, 5, 3, 8>(dst, 2 * t - g);
    else if (unit == 1) box_ones<1, 7, 0, 9, 2>(dst, 4 * t - g);
    else if (unit == 2) sts128(dst, tok_at(16 * g - 10 + 2 * t), tok_at(16 * g - 2 + 2 * t), tok_at(16 * g - 12 + 4 * t), tok_at(16 * g - 4 + 4 * t));
    else {
        const uint32_t low = 64 * (t >> 1) + 32 * (g & 1) + 16 * (t & 1), hi = (lane & 24) + (lane & 16);
        sts128(dst, 128 * hi + low, 512 * (4 * (r & 2) + 2 * m + (r & 1)) + 16 * ((r >> 2) ^ (2 * (r & 3))), 32 * hi + low, 8 * (6 + g - 2 * t));
    }
}

__device__ __forceinline__ uint32_t mean_std(float mu, float var) { return pack_bf16(mu, sqrtaf(bf_round(bf_round(var) + 1e-5f))); }
__device__ __noinline__ uint2 ln_centred(uint32_t sb, float mu) {
    const int lane = threadIdx.x & 31;
    uint32_t ms = 0;
    float res = 0.f, ri = 0.f;
#pragma unroll 1
    for (int mode = 0; mode < 2; mode++) {
#pragma unroll 1
        for (int rr = 0; rr < 16; rr++) {
            const float c0 = __shfl_sync(0xffffffffu, mu, rr), rj = __shfl_sync(0xffffffffu, ri, rr);
            float c = 0.f;
#pragma unroll 1
            for (int k = 0; k < 16; k++) {
                const uint32_t q = lds32(sb + OFF_ROWS + k * 2048 + rr * 128 + ((lane * 4) ^ ((rr & 7) << 4))), wq = lds32(sb + OFF_GP + k * 128 + lane * 4);
                const float d0 = bf_lo(q) - c0, d1 = bf_hi(q) - c0;
                if (mode) c = fmaf(bf_round(bf_round(d0) * rj), bf_lo(wq), fmaf(bf_round(bf_round(d1) * rj), bf_hi(wq), c));
                else c = fmaf(d0, d0, fmaf(d1, d1, c));
            }
#pragma unroll 1
            for (int o = 16; o; o >>= 1) c += __shfl_xor_sync(0xffffffffu, c, o);
            if ((lane & 15) == rr) res = c;
        }
        if (mode == 0) { ms = mean_std(mu, res * (1.f / DM)); mu = bf_lo(ms); ri = rcpf(bf_hi(ms)); }
    }
    named_sync(1, 128);
    return make_uint2(ms, __float_as_uint(res));
}

__device__ __forceinline__ void router_cta(uint32_t* scr, uint32_t sb, uint32_t zero, int tid, int warp) {
    const int lane = tid & 31;
    const uint32_t cand = sb + 128;
    const uint32_t epoch = ld_relaxed_32(scr + S_EPOCH);
    if (tid < 128) st_relaxed_32(scr + S_SEL + tid, 0u);
    if (tid == 0) sts32(sb + 64, cand);
    sts128(cand + 16 * tid, 0, 0, 0, 0);
    asm volatile("fence.acq_rel.gpu;" ::: "memory");
    const uint32_t tag = (epoch + 1u) | 0x8000u;
    STAMP(0); GSTAMP(1);
    uint32_t* const psel = scr + S_SEL + 32 * (lane & 3);
    const uint32_t cnt = sb + 64 + (tid & zero);
    uint32_t it = 0;
    uint4 q;
#pragma unroll 1
    do {
        q = ld_relaxed_128(scr + S_KEY + 4 * tid);
        if (++it > SPIN_LIMIT) __trap();
    } while (!__all_sync(0xffffffffu, (((q.x ^ tag) | (q.y ^ tag) | (q.z ^ tag) | (q.w ^ tag)) & 0xffffu) == 0));
    STAMP(2);
    uint32_t key[4] = {q.x, q.y, q.z, q.w};
#pragma unroll
    for (int j = 0; j < 4; j++) key[j] = ((key[j] ^ ((uint32_t)((int)key[j] >> 31) | 0x80000000u)) & 0xffff0000u) | (0xffffu - (uint32_t)(4 * tid + j));
    const uint32_t gm = __reduce_max_sync(0xffffffffu, max(max(key[0], key[1]), max(key[2], key[3])));
    sts32(sb + 4 * warp, gm);
    __syncthreads();
    const uint2 pr = lds64(sb + 8 * (lane & 7));
    const uint32_t tau = __reduce_min_sync(0xffffffffu, max(pr.x, pr.y));
    asm volatile("{\n\t.reg .pred p<4>;\n\t.reg .u32 a<4>;\n\t"
                 "setp.ge.u32 p0, %0, %4;\n\tsetp.ge.u32 p1, %1, %4;\n\tsetp.ge.u32 p2, %2, %4;\n\tsetp.ge.u32 p3, %3, %4;\n\t"
                 "@p0 atom.shared.add.u32 a0, [%5], 4;\n\t@p1 atom.shared.add.u32 a1, [%5], 4;\n\t"
                 "@p2 atom.shared.add.u32 a2, [%5], 4;\n\t@p3 atom.shared.add.u32 a3, [%5], 4;\n\t"
                 "@p0 st.shared.u32 [a0], %0;\n\t@p1 st.shared.u32 [a1], %1;\n\t@p2 st.shared.u32 [a2], %2;\n\t@p3 st.shared.u32 [a3], %3;\n\t}"
                 ::"r"(key[0]), "r"(key[1]), "r"(key[2]), "r"(key[3]), "r"(tau), "r"(cnt) : "memory");
    __syncthreads();
    STAMP(6);
    const uint32_t c0 = lds32v(cand + 4 * lane);
    uint2 k = lds64(cand + 8 * warp);
    const uint32_t end = __shfl_sync(0xffffffffu, lds32v(sb + 64), 0);
    uint32_t i = cand + 8 * warp;
#pragma unroll 1
    do {
        uint32_t r0 = __popc(__ballot_sync(0xffffffffu, c0 > k.x)), r1 = __popc(__ballot_sync(0xffffffffu, c0 > k.y));
#pragma unroll 1
        for (uint32_t j = cand + 128; j < end; j += 128) {
            const uint32_t c = lds32(j + 4 * lane);
            r0 += __popc(__ballot_sync(0xffffffffu, c > k.x)); r1 += __popc(__ballot_sync(0xffffffffu, c > k.y));
        }
        const uint32_t rk = (lane & 4) ? r1 : r0;
        if (rk < 8 && lane < 8) st_relaxed_64(psel + 2 * rk, (lane & 4) ? k.y : k.x, tag);
        i += 128;
        k = lds64(i);
    } while (i < end);
    STAMP(4); GSTAMP(5);
    if (tid == 0) st_relaxed_32(scr + S_EPOCH, epoch + 1u);
}

__global__ void __cluster_dims__(2, 1, 1) __launch_bounds__(NTHR, 1)
fused_kernel(const __grid_constant__ Ptrs p, const __grid_constant__ Maps maps) {
    extern __shared__ __align__(1024) unsigned char smem[];
    const uint32_t sb = s_u32(smem);
    const int tid = threadIdx.x, lane = tid & 31;
    const int warp = __shfl_sync(0xffffffffu, tid >> 5, 0);
    const int b = blockIdx.x, h = b & 1, cl = b >> 1;
    const uint32_t bar0 = sb + OFF_BAR;
    const int m = lane >> 3, r = lane & 7;
    if (b >= NCTA) {
        if (b == NCTA) router_cta(p.scr, sb, p.zero, tid, warp);
        return;
    }
    if (warp < 8) {
        const int w = warp, dch = 8 * b + w;
        STAMP(0);
        if (INC_AT == 0) asm volatile("setmaxnreg.inc.sync.aligned.u32 %0;" ::"n"(NREG));
        const int po = dch * NMODE + 4 * lane;
        const uint2 la = ldg64(p.logA + po), aim = ldg64(p.Aim + po), cre = ldg64(p.Cre + po), cim = ldg64(p.Cim + po);
        const uint32_t ldt16 = ldg16(p.ldt + dch), dsk16 = ldg16(p.dsk + dch);
        cluster_arrive();
        if (CW_EARLY) cluster_wait();
        if (INC_AT == 1) asm volatile("setmaxnreg.inc.sync.aligned.u32 %0;" ::"n"(NREG));
        const uint32_t priv = sb + OFF_PRIV + w * PRIV;
        const int g = lane >> 2, t = lane & 3;
        float kacc[5][4], kscale;
        {
            const uint32_t m2 = as_u(__hmax2(__hmax2(__habs2(as_b2(cre.x)), __habs2(as_b2(cre.y))), __hmax2(__habs2(as_b2(cim.x)), __habs2(as_b2(cim.y)))));
            const uint32_t eb = min(max(__reduce_max_sync(0xffffffffu, max(m2 << 16, m2)) >> 23, 1u), 252u);
            const float dt = bf_round(ex2f(bf_lo(ldt16) * L2E));
            STAMP(1);
            kgen_mma(kacc, priv, lane, la, aim, cre, cim, dt, (253u - eb) * 0x00800080u);
            STAMP(2);
            if (INC_AT == 2) asm volatile("setmaxnreg.inc.sync.aligned.u32 %0;" ::"n"(NREG));
            if (!CW_EARLY) cluster_wait();
            __syncwarp();
            if (elect_one()) mbar_arrive(bar0 + 8 * B_KG);
            float s0[4];
            mma_bf16_z(s0, ONES, ONES, ONES, ONES, cre.x, cre.y);
            float k0 = s0[0] + s0[1];
            k0 += __shfl_xor_sync(0xffffffffu, k0, 1);
            k0 += __shfl_xor_sync(0xffffffffu, k0, 2);
            kscale = (dt + dt) * __uint_as_float((eb + 1u) << 23);
            kgen_tables(kacc, priv, lane, kscale, fmaf(k0, dt + dt, bf_lo(dsk16) + 1.f));
        }
        STAMP(3);
        if (INC_AT == 3) { __syncwarp(); asm volatile("setmaxnreg.inc.sync.aligned.u32 %0;" ::"n"(NREG)); }
        kgen_tables2(kacc, priv, lane, kscale);
        STAMP(4);
        if (INC_AT == 4) asm volatile("setmaxnreg.inc.sync.aligned.u32 %0;" ::"n"(NREG));
        float acc[16][4];
        dense_phase(acc, priv, lane, [&]() {
            mbar_wait(bar0 + 8 * B_VT, 0);
            STAMP(6);
        }, [&]() { mbar_wait(bar0 + 8 * B_PV, 0); });
        STAMP(7);
        const uint32_t sd = sb + OFF_X + 512 * (8 * h + w) + 16 * (lane ^ (2 * (w & 1) + 4 * h));
        const uint32_t sd0 = mapa(sd + 8192, 0), sd1 = mapa(sd, 1);
        auto send = [&](auto PT) {
            constexpr int pt = decltype(PT)::value;
#pragma unroll
            for (int i = 0; i < 2; i++) {
                const float* c0 = acc[4 * pt + 2 * i];
                const float* c1 = acc[4 * pt + 2 * i + 1];
                asm volatile("st.async.weak.shared::cluster.mbarrier::complete_tx::bytes.v4.b32 [%0 + %6], {%1,%2,%3,%4}, [%5];"
                             ::"r"(i ? sd1 : sd0), "r"(pack_bf16(c0[0], c0[1])), "r"(pack_bf16(c0[2], c0[3])), "r"(pack_bf16(c1[0], c1[1])),
                               "r"(pack_bf16(c1[2], c1[3])), "r"(mapa(bar0 + 8 * (B_RECV + pt), i)), "n"(16384 * pt) : "memory");
            }
        };
        const uint4 lc = lds128(sb + OFF_LC + 1536 + 16 * lane);
        const uint32_t stg = (priv + T_DENSE + 63) & ~127u, so = stg + lc.z;
        const uint32_t xa = sb + OFF_X + 16384 * (w >> 2) + 8192 * h + 256 * (w & 3) + lc.x;
        const uint32_t sa = sb + OFF_X + 16384 * (w >> 2) + 8192 * (h ^ 1) + 128 * (w & 3) + lc.y;
        constexpr int ST2 = -2048;
        auto finish = [&](int ph) {
            if (ph == FINE) STAMP(1);
            const int box = 4 * ph + 2 * (w >> 2) + h;
            uint4 x[4];
            uint32_t s[4][4];
#pragma unroll
            for (int i = 0; i < 4; i++) x[i] = lds128((xa ^ (8 * (i & 2))) + 32768 * ph + 2048 * (i & 1) + 64 * (i & 2));
            if (ph == FINE) STAMP(2);
            mbar_wait(bar0 + 8 * (B_RECV + 2 * ph + (w >> 2)), 0);
            if (ph == FINE) STAMP(3);
            const uint32_t routed = __shfl_sync(0xffffffffu, lds32(sb + OFF_MISC + 4), 0);
#pragma unroll
            for (int i = 0; i < 4; i++) ldsm4t(s[i], (sa ^ (32 * i)) + 32768 * ph);
#pragma unroll
            for (int i = 0; i < 4; i++) { s[i][0] = badd2(x[i].x, s[i][0]); s[i][1] = badd2(x[i].y, s[i][1]); s[i][2] = badd2(x[i].z, s[i][2]); s[i][3] = badd2(x[i].w, s[i][3]); }
            if (ph == FINE) STAMP(4);
            if (((routed >> (4 * box + (w & 3))) & 1) || (LAST_DIRECT && ph && w >= 4)) {
                const uint32_t tk = 256 * box + 128 * (g >> 2) + 32 * (t >> 1) + 16 * (g & 1) + 4 * (g & 2) + 2 * (w & 3);
                const uint32_t mk[2] = {lds32(sb + OFF_MISC + 32 + 4 * (tk >> 5)) >> (tk & 31), lds32(sb + OFF_MISC + 40 + 4 * (tk >> 5)) >> (tk & 31)};
                __nv_bfloat16* o = p.out + (size_t)tk * DM + 16 * cl + 8 * (t & 1);
#pragma unroll
                for (int i = 0; i < 4; i++)
                    asm volatile("{\n\t.reg .pred p;\n\tsetp.eq.u32 p, %6, 0;\n\t@!p st.shared.v4.u32 [%1], {%2,%3,%4,%5};\n\t@p st.global.v4.u32 [%0], {%2,%3,%4,%5};\n\t}"
                                 ::"l"(o + (64 * (i & 1) + (i >> 1)) * DM), "r"((xa ^ (8 * (i & 2))) + 32768 * ph + 2048 * (i & 1) + 64 * (i & 2)),
                                   "r"(s[i][0]), "r"(s[i][1]), "r"(s[i][2]), "r"(s[i][3]), "r"(mk[i & 1] & (1u << (i >> 1))) : "memory");
            } else {
#pragma unroll
                for (int i = 0; i < 4; i++) sts128(so + ST2 * ph + 512 * (i & 1) + 64 * (i & 2), s[i][0], s[i][1], s[i][2], s[i][3]);
                fence_async();
                if (ph == FINE) STAMP(5);
                __syncwarp();
                if (elect_one()) {
                    asm volatile("cp.async.bulk.tensor.5d.global.shared::cta.bulk_group [%0, {%2, %5, %3, %5, %4}], [%1];"
                                 ::"l"(&maps.out), "r"(stg + ST2 * ph), "r"(16 * cl), "r"(2 * (w & 3)), "r"(4 * box), "r"(0) : "memory");
                }
            }
        };
        Tails tl;
        tl.start(sb + OFF_LC + 16 * lane, priv, lc.w, lane);
        send(IC<0>());
        tl.run<0, 4>(acc, priv, lc.w, lane);
        send(IC<1>());
        STAMP(8);
        tl.run<4, FIN_A>(acc, priv, lc.w, lane);
        if (FIN_A == FIN_B || w < 4) finish(0);
        tl.run<FIN_A, FIN_B>(acc, priv, lc.w, lane);
        if (FIN_A != FIN_B && FIN_B < 12 && w >= 4) finish(0);
        tl.run<FIN_B, 12>(acc, priv, lc.w, lane);
        send(IC<2>());
        STAMP(9);
        if (FIN_A != FIN_B && FIN_B == 12 && w >= 4) finish(0);
        tl.run<12, 20>(acc, priv, lc.w, lane);
        STAMP(11);
        send(IC<3>());
        finish(1);
        STAMP(12);
        __syncwarp();
        if (elect_one()) mbar_arrive(bar0 + 8 * B_ST);
        if (END_BAR) cluster_arrive();
        asm volatile("cp.async.bulk.commit_group;" ::: "memory");
        asm volatile("cp.async.bulk.wait_group.read 0;" ::: "memory");
        STAMP(13); GSTAMP(15);
    } else if (warp < 12) {
        const int a = warp - 8, at = 32 * a + lane, g = lane >> 2, t = lane & 3;
        STAMP(0);
        if (elect_one()) {
            const uint32_t cnt = a == 3 ? 0x18411122u : a == 2 ? 0x44444444u : 0x11111111u, tx = a == 0 ? 0x44444444u : a == 3 ? 0x00084444u : 0u;
#pragma unroll 1
            for (int i = 0; i < 8; i++) {
                mbar_init(bar0 + 64 * a + 8 * i, (cnt >> (4 * i)) & 15);
                const uint32_t n = (tx >> (4 * i)) & 15;
                if (n) mbar_expect_tx(bar0 + 64 * a + 8 * i, n << 11);
            }
            if (a < 3) mbar_init(bar0 + 8 * (B_KG + a), a ? 4 : 8);
            asm volatile("fence.mbarrier_init.release.cluster;" ::: "memory");
            fence_async();
        }
        __syncwarp();
        cluster_arrive();
        if (FREG > 128) asm volatile("setmaxnreg.inc.sync.aligned.u32 %0;" ::"n"(FREG));
        const uint32_t epoch = ld_relaxed_32(p.scr + S_EPOCH);
        uint32_t* const pst = p.scr + S_STAT + 2048 * a + 16 * b + 2 * r + m;
        uint32_t* const pky = p.scr + S_KEY + 16 * b + at;
        if (at < 16) st_relaxed_32(pky, 0u);
        uint32_t* const py = p.scr + S_Y + 1024 * ((cl & ~3) + a) + 128 * (b & 7) + 32 * t + 4 * g;
        const uint32_t gp = sb + OFF_GP;
        sts32(gp + 2048 + 4 * lane, ONES);
        lane_consts(sb + OFF_LC + 16 * at, a, lane);
        cluster_wait();
        STAMP(1);
        if (lane < 16) st_relaxed_32(pst, epoch << 31);
        mbar_wait(bar0 + 8 * B_WR, 0);
        float wsum;
        {
            const uint4 q = lds128(gp + 16 * at);
            wsum = ((bf_lo(q.x) + bf_hi(q.x)) + (bf_lo(q.y) + bf_hi(q.y))) + ((bf_lo(q.z) + bf_hi(q.z)) + (bf_lo(q.w) + bf_hi(q.w)));
#pragma unroll
            for (int o = 16; o; o >>= 1) wsum += __shfl_xor_sync(0xffffffffu, wsum, o);
            sts32(gp + 2176 + 4 * a, __float_as_uint(wsum));
        }
        const uint32_t hsel = (epoch & 1) * (GU_CTAS * 128), want = (epoch & 1) ? 0u : 0x80008000u;
        const uint32_t tbit = ~epoch << 31, ktag = ((epoch + 1u) | 0x8000u) & 0xffffu;
        if (a == 0) sts64(sb + OFF_MISC + 32 + 8 * lane, 0u, 0u);
        if (b < GU_CTAS) st_relaxed_32(p.scr + S_H + (GU_CTAS * 128 - hsel) + b * 128 + at, 0u);
        {
            uint32_t ra[4], rb[4], rs;
#pragma unroll
            for (int i = 0; i < 4; i++) {
                ra[i] = (m & 1) ? (r == 1 ? gp + 128 * a + 32 * i + 16 * (m >> 1) : gp + 2048) : sb + OFF_ROWS + 2048 * a + 128 * r + (((2 * i + (m >> 1)) ^ r) << 4);
                rb[i] = sb + OFF_ROWS + 2048 * a + 128 * (r + 8 * (m >> 1)) + (((2 * i + (m & 1)) ^ r) << 4);
            }
            rs = (m & 1) ? (r == 1 ? 512 : 0) : 8192;
            const uint32_t r8 = (m & 1) ? 0 : 1024;
            float cs[4][4] = {};
#pragma unroll 1
            for (int k = 0; k < 4; k++) {
                uint32_t x[4][4], y[4][4], z[4][4];
                mbar_wait(bar0 + 8 * (B_ROW + k), 0);
#pragma unroll
                for (int i = 0; i < 4; i++) {
                    ldsm4(x[i], ra[i]); ldsm4(y[i], ra[i] + r8);
                    if (LN_DUP) ldsm4(z[i], rb[i] + 8192 * k);
                    else { z[i][0] = x[i][0]; z[i][1] = x[i][2]; z[i][2] = y[i][0]; z[i][3] = y[i][2]; }
                    ra[i] += rs;
                }
#pragma unroll
                for (int i = 0; i < 4; i++) {
                    mma4(cs[2 * (i & 1)], x[i], z[i][0], z[i][1]);
                    mma4(cs[2 * (i & 1) + 1], y[i], z[i][2], z[i][3]);
                }
            }
            const uint32_t pa = gp + 2304 + 4 * a;
#pragma unroll
            for (int i = 0; i < 8; i++) cs[i >> 2][i & 3] += cs[2 + (i >> 2)][i & 3];
            if (g < 2) {
#pragma unroll
                for (int i = 0; i < 4; i++) sts32(pa + 256 * g + 32 * t + 128 * (i >> 1) + 16 * (i & 1), __float_as_uint(cs[i >> 1][2 + (i & 1)]));
            }
            if (t == (g >> 1)) {
                sts32(pa + 512 + 16 * g, __float_as_uint((g & 1) ? cs[0][1] : cs[0][0]));
                sts32(pa + 640 + 16 * g, __float_as_uint((g & 1) ? cs[1][1] : cs[1][0]));
            }
            named_sync(1, 128);
            auto sum4 = [](uint4 q) { return (__uint_as_float(q.x) + __uint_as_float(q.y)) + (__uint_as_float(q.z) + __uint_as_float(q.w)); };
            const uint32_t o = gp + 2304 + 16 * (lane & 15);
            const float mu = sum4(lds128(o)) * (1.f / DM), e2 = sum4(lds128(o + 512)) * (1.f / DM), var = fmaf(-mu, mu, e2);
            const float sw = sum4(lds128(o + 256));
            wsum = sum4(lds128(gp + 2176));
            uint32_t ms = mean_std(mu, var);
            float sc = (sw - bf_round(mu) * wsum) * rcpf(bf_hi(ms));
            if (__any_sync(0xffffffffu, !(e2 <= 65.f * var))) {
                const uint2 c = ln_centred(sb, mu);
                ms = c.x; sc = __uint_as_float(c.y);
            }
            if (lane < 16 && a <= REPM) st_relaxed_32(pst, ms | tbit);
            if (at < 16) st_relaxed_32(pky, pack_bf16(0.f, sc) | ktag);
            if (lane < 8) mbar_arrive(bar0 + 8 * (B_EMPTY + lane));
        }
        STAMP(3); GSTAMP(14);
        {
            const uint32_t* sp = p.scr + S_STAT + 2048 * (cl & REPM) + 512 * a + 16 * t + 2 * g;
            uint2 sq[8];
            uint32_t s2[8], bad;
            if (ST_GATE >= 0) mbar_wait(bar0 + 8 * (B_X + 4 * h + ST_GATE), 0);
#pragma unroll 1
            do {
                __nanosleep(STAT_SLEEP);
#pragma unroll
                for (int i = 0; i < 8; i++) sq[i] = ld_relaxed_64(sp + 64 * i);
                bad = 0;
#pragma unroll
                for (int i = 0; i < 8; i++) { s2[i] = __byte_perm(sq[i].x, sq[i].y, 0x7632) ^ want; bad |= s2[i]; }
            } while (!__all_sync(0xffffffffu, (bad & 0x80008000u) == 0));
            STAMP(13);
            const uint32_t xa = sb + OFF_X + 16384 * a + 32 * lane + ((h ^ (g & 1)) << 4);
            const uint32_t dst = sb + OFF_PRIV + (2 * m + (r & 1)) * PRIV + 128 + 512 * a + 16 * (r >> 1);
#pragma unroll
            for (int bk = 0; bk < 2; bk++) {
                mbar_wait(bar0 + 8 * (B_X + 2 * a + bk), 0);
                uint32_t v[8][4];
#pragma unroll
                for (int i = 0; i < 4; i++) {
                    const uint2 rc = recip2(s2[4 * bk + i]), st = sq[4 * bk + i];
#pragma unroll
                    for (int hf = 0; hf < 2; hf++) {
                        const __nv_bfloat162 mm = __low2bfloat162(as_b2(hf ? st.y : st.x));
                        const __nv_bfloat162 rh = hf ? __high2bfloat162(as_b2(rc.x)) : __low2bfloat162(as_b2(rc.x));
                        const __nv_bfloat162 rl = hf ? __high2bfloat162(as_b2(rc.y)) : __low2bfloat162(as_b2(rc.y));
                        const uint4 q = lds128(xa + 8192 * bk + 2048 * i + 1024 * hf);
                        uint32_t* o = v[2 * i + hf];
                        o[0] = normalize2(q.x, mm, rh, rl); o[1] = normalize2(q.y, mm, rh, rl); o[2] = normalize2(q.z, mm, rh, rl); o[3] = normalize2(q.w, mm, rh, rl);
                    }
                }
                if (bk == 0) mbar_wait(bar0 + 8 * B_KG, 0);
#pragma unroll
                for (int i = 0; i < 8; i++) stsm4t(dst + 256 * bk + 64 * (i >> 1) + PLANE * (i & 1), v[i]);
            }
            __syncwarp();
            if (elect_one()) { mbar_arrive(bar0 + 8 * B_VT); mbar_arrive_peer(mapa(bar0 + 8 * B_PV, h ^ 1)); }
            __syncwarp();
            if (END_BAR) cluster_arrive();
        }
        uint32_t mykey;
        {
            const uint32_t* sl = p.scr + S_SEL + 32 * (cl & 3) + 2 * g;
            uint2 q;
#pragma unroll 1
            do {
                __nanosleep(SEL_SLEEP);
                q = ld_relaxed_64(sl);
            } while (!__all_sync(0xffffffffu, q.y == ((epoch + 1u) | 0x8000u)));
            mykey = q.x;
        }
        STAMP(4);
        if (a == 0) {
            const uint32_t tok = ~mykey & 0xffffu;
            if (t == 0) asm volatile("red.shared.or.b32 [%0], %1;" ::"r"(sb + OFF_MISC + 32 + 4 * (tok >> 5)), "r"(1u << (tok & 31u)) : "memory");
            sts32(sb + OFF_MISC + 4, __reduce_or_sync(0xffffffffu, 1u << (4 * (tok >> 8) + ((tok >> 1) & 3))));
            __syncwarp();
            if (elect_one()) { mbar_arrive(bar0 + 8 * B_RECV); mbar_arrive(bar0 + 8 * (B_RECV + 1)); }
        }
        if (b < GU_CTAS) {
            const uint32_t tok = 0xffffu - (mykey & 0xffffu);
            {
                const uint32_t tk = __shfl_sync(0xffffffffu, tok, 16 * h + 4 * a);
                if (elect_one())
                    asm volatile("cp.async.bulk.shared::cluster.global.mbarrier::complete_tx::bytes.multicast::cluster [%0], [%1], 2048, [%2], %3;"
                                 ::"r"(sb + OFF_XS + (4 * h + a) * ROW_PITCH), "l"(p.u + (size_t)tk * DM), "r"(bar0 + 8 * B_XS), "h"((uint16_t)3) : "memory");
            }
            uint2 rec;
#pragma unroll 1
            do {
                rec = ld_relaxed_64(p.scr + S_STAT + 2048 * (a & REPM) + (tok & ~15u) + 2 * (tok & 7u));
            } while (!__all_sync(0xffffffffu, ((__byte_perm(rec.x, rec.y, 0x7632) ^ want) & 0x80008000u) == 0));
            const uint32_t mst = (tok & 8u) ? rec.y : rec.x;
            const uint32_t m2 = __byte_perm(mst, 0, 0x1010);
            const float rs = rcpf(__uint_as_float(mst & 0x7fff0000u));
            const float r0 = __shfl_sync(0xffffffffu, rs, 8 * t), r1 = __shfl_sync(0xffffffffu, rs, 8 * t + 4);
            float gacc[4 * NACC][4] = {};
            const int k = r + 8 * (m >> 1);
            uint32_t wa[4];
#pragma unroll
            for (int mt = 0; mt < 4; mt++) wa[mt] = 1024 * a + (((m & 1) * 4096) ^ p.up_first) + k * 64 + ((((k >> 1) & 3) ^ mt) << 4);
            const uint32_t xa = sb + OFF_XS + r * ROW_PITCH + 32 * a + 16 * (m & 1) + 128 * (m >> 1);
#pragma unroll 1
            for (int c = 0; c < 4; c++) {
                uint32_t af[4][4][4], xb[2][4];
                const uint32_t half = sb + OFF_RING + 32768 * (c & 1), fb = bar0 + 8 * B_FULL + 32 * (c & 1);
#pragma unroll
                for (int j = 0; j < 4; j++) {
                    mbar_wait(fb + 8 * j, c >> 1);
                    if (j == 3) STAMP(12);
#pragma unroll
                    for (int mt = 0; mt < 4; mt++) ldsm4t(af[j][mt], wa[mt] + half + j * 8192);
                    __syncwarp();
                    if (elect_one()) mbar_arrive(fb + 8 * (B_EMPTY - B_FULL + j));
                    if (j == GU_SPLIT) {
                        mbar_wait(bar0 + 8 * B_XS, 0);
#pragma unroll
                        for (int i = 0; i < 2; i++) {
                            ldsm4(xb[i], xa + 512 * c + 256 * i);
#pragma unroll
                            for (int e = 0; e < 4; e++) xb[i][e] = as_u(__hsub2(as_b2(xb[i][e]), as_b2(m2)));
                        }
                    }
                    if (j == 3) STAMP(1);
                    if (j >= GU_SPLIT) {
#pragma unroll
                        for (int ks = j == GU_SPLIT ? 0 : j; ks <= j; ks++) {
#pragma unroll
                            for (int mt = 0; mt < 4; mt++)
                                mma_bf16v(gacc[mt + 4 * (ks % NACC)], af[ks][mt], xb[ks >> 1][2 * (ks & 1)], xb[ks >> 1][2 * (ks & 1) + 1]);
                        }
                    }
                }
            }
            STAMP(6);
#pragma unroll
            for (int mt = 0; mt < 4; mt++) {
#pragma unroll
                for (int i = 0; i < 4 * (NACC - 1); i++) gacc[mt][i] += gacc[mt + 4][i];
                sts128f(gp + 2048 * a + mt * 512 + lane * 16, gacc[mt]);
            }
            named_sync(1, 128);
            {
                uint4 q[4];
#pragma unroll
                for (int wq = 0; wq < 4; wq++) q[wq] = lds128(gp + 2048 * wq + 16 * at);
                const uint32_t g2 = pack_bf16(r0 * ((__uint_as_float(q[0].x) + __uint_as_float(q[1].x)) + (__uint_as_float(q[2].x) + __uint_as_float(q[3].x))),
                                              r1 * ((__uint_as_float(q[0].y) + __uint_as_float(q[1].y)) + (__uint_as_float(q[2].y) + __uint_as_float(q[3].y))));
                const uint32_t u2 = pack_bf16(r0 * ((__uint_as_float(q[0].z) + __uint_as_float(q[1].z)) + (__uint_as_float(q[2].z) + __uint_as_float(q[3].z))),
                                              r1 * ((__uint_as_float(q[0].w) + __uint_as_float(q[1].w)) + (__uint_as_float(q[2].w) + __uint_as_float(q[3].w))));
                const uint32_t s2 = pack_bf16(bf_lo(g2) * rcpf(1.f + ex2f(-L2E * bf_lo(g2))), bf_hi(g2) * rcpf(1.f + ex2f(-L2E * bf_hi(g2))));
                uint32_t hw;
                asm volatile("movmatrix.sync.aligned.m8n8.trans.b16 %0, %1;" : "=r"(hw) : "r"(as_u(__hmul2(as_b2(s2), as_b2(u2)))));
                if (hw == 0u) hw = 0x80008000u;
                st_relaxed_32(p.scr + S_H + hsel + b * 128 + at, hw);
            }
            STAMP(7);
        }
        const uint32_t ytag = 1u + (epoch & 1);
        {
            const uint32_t* hp = p.scr + S_H + hsel + (b & 7) * 1792 + 64 * a + lane;
            constexpr int NH = MT_LAST ? 20 : 14;
            uint32_t wa[4], af[DN_RUN][4][4], hb[NH];
#pragma unroll
            for (int mt = 0; mt < 4; mt++) wa[mt] = sb + OFF_RING + 2048 * a + 128 * (r + 8 * (m >> 1)) + (((2 * mt + (m & 1)) ^ r) << 4);
            float dacc[4][4] = {};
            auto load_w = [&](int s) {
                mbar_wait(bar0 + 8 * (B_FULL + s), 0);
#pragma unroll
                for (int j = 0; j < 4; j++) ldsm4t(af[s % DN_RUN][j], wa[j] + s * 8192);
            };
            auto run = [&](int s) {
#pragma unroll
                for (int j = 0; j < 4; j++) mma_bf16v(dacc[j], af[s % DN_RUN][j], hb[2 * s], hb[2 * s + 1]);
            };
            auto look = [&]() {
#pragma unroll
                for (int j = 0; j < NH; j++) hb[j] = ld_relaxed_32(MT_LAST && j >= 12 ? hp - 64 * a + 1536 + 32 * (j - 12) : hp + 256 * (j >> 1) + 32 * (j & 1));
            };
            auto missing = [&]() {
                uint32_t mn = hb[0];
#pragma unroll
                for (int j = 1; j < NH; j++) mn = min(mn, hb[j]);
                return __any_sync(0xffffffffu, mn == 0);
            };
            load_w(0);
            st_relaxed_128(py, 0u, 0u, 0u, 0u);
            bool again = true;
            if (b >= GU_CTAS) { look(); again = missing(); }
#pragma unroll
            for (int s = 1; s < DN_PRE; s++) load_w(s);
            if (again) look();
#pragma unroll
            for (int s = DN_PRE; s < DN_RUN; s++) load_w(s);
#pragma unroll 1
            while (missing()) { __nanosleep(H_SLEEP); look(); }
            STAMP(2);
#pragma unroll
            for (int s = 0; s < DN_RUN; s++) run(s);
#pragma unroll
            for (int s = DN_RUN; s < 7 - DN_LAST; s++) load_w(s);
#pragma unroll
            for (int s = DN_RUN; s < 7 - DN_LAST; s++) run(s);
            if (DN_LAST && !MT_LAST) { load_w(6); run(6); }
            STAMP(8);
#pragma unroll
            for (int mt = 0; mt < 4; mt++) sts128f(sb + OFF_XS + 2048 * a + mt * 512 + lane * 16, dacc[mt]);
            named_sync(1, 128);
            uint4 q[4];
#pragma unroll
            for (int wq = 0; wq < 4; wq++) q[wq] = lds128(sb + OFF_XS + 2048 * wq + 16 * at);
            if (MT_LAST) {
                mbar_wait(bar0 + 8 * (B_FULL + 6), 0);
#pragma unroll
                for (int j = 0; j < 4; j++) {
                    uint32_t A[4];
                    ldsm4t(A, sb + OFF_RING + 6 * 8192 + 2048 * j + 128 * (r + 8 * (m >> 1)) + (((2 * a + (m & 1)) ^ r) << 4));
                    mma_bf16v(reinterpret_cast<float*>(&q[j]), A, hb[NH - 8 + 2 * j], hb[NH - 7 + 2 * j]);
                }
            }
            auto tagged = [&](uint32_t x0, uint32_t x1, uint32_t x2, uint32_t x3) {
                return (__float_as_uint((__uint_as_float(x0) + __uint_as_float(x1)) + (__uint_as_float(x2) + __uint_as_float(x3))) & ~3u) | ytag;
            };
            st_relaxed_128(py, tagged(q[0].x, q[1].x, q[2].x, q[3].x), tagged(q[0].y, q[1].y, q[2].y, q[3].y),
                           tagged(q[0].z, q[1].z, q[2].z, q[3].z), tagged(q[0].w, q[1].w, q[2].w, q[3].w));
        }
        STAMP(9);
        {
            const uint32_t key = __shfl_sync(0xffffffffu, mykey, 8 * a + 4 * (m >> 1));
            const uint32_t tok = 0xffffu - (key & 0xffffu);
            const float sg = bf_round(rcpf(1.f + ex2f(-L2E * bf_lo(unorder_key(key >> 16)))));
            const uint32_t xo = sb + OFF_X + 32 * (tok & ~63u) + 128 * (tok & 15u) + 2 * (tok & 48u) + ((2 * (lane & 15)) ^ ((tok & 1u) << 4));
            const bool mine = ((tok >> 8) & 1) == h;
            uint32_t upd = 0;
            if (mine) {
                const uint32_t* yp = p.scr + S_Y + 1024 * cl + 32 * a + 4 * r + 2 * (m & 1) + (m >> 1);
                uint32_t pp[8], bad;
#pragma unroll 1
                do {
                    bad = 0;
#pragma unroll
                    for (int q = 0; q < 8; q++) pp[q] = ld_relaxed_32(yp + 128 * q);
#pragma unroll
                    for (int q = 0; q < 8; q++) bad |= pp[q] ^ ytag;
                } while (bad & 3u);
                const float y = ((__uint_as_float(pp[0]) + __uint_as_float(pp[1])) + (__uint_as_float(pp[2]) + __uint_as_float(pp[3]))) +
                                ((__uint_as_float(pp[4]) + __uint_as_float(pp[5])) + (__uint_as_float(pp[6]) + __uint_as_float(pp[7])));
                upd = pack_bf16(bf_round(y) * sg, 0.f);
                STAMP(11);
            }
            __syncwarp();
            if (EARLY_DONE && elect_one()) mbar_arrive(bar0 + 8 * B_DONE);
            if (mine) {
                mbar_wait(bar0 + 8 * B_ST, 0);
                uint32_t o;
                asm volatile("ld.shared.u16 %0, [%1];" : "=r"(o) : "r"(xo));
                asm volatile("st.global.u16 [%0], %1;" ::"l"(p.out + (size_t)tok * DM + 16 * cl + (lane & 15)), "r"(badd2(o, upd)) : "memory");
            }
            if (!EARLY_DONE) { __syncwarp(); if (elect_one()) mbar_arrive(bar0 + 8 * B_DONE); }
        }
        STAMP(10); GSTAMP(15);
    } else {
        asm volatile("setmaxnreg.dec.sync.aligned.u32 %0;" ::"n"(FREG <= 136 ? 40 : 512 - 2 * NREG - FREG));
        const int q = warp - 12;
        sts32(sb + OFF_MISC + 16 + 4 * q, clk());
        const uint32_t t0 = __shfl_sync(0xffffffffu, lds32v(sb + OFF_MISC + 16 + 4 * q), 0);
        STAMP(0);
        if (q == 1) GSTAMP(14);
        const bool one = elect_one();
        const uint32_t rbar = bar0 + 8 * (B_ROW + q);
        if (one) {
            asm volatile("prefetch.tensormap [%0];" ::"l"(&maps.rows) : "memory");
            mbar_init(rbar, 1);
            if (q == 3) mbar_init(bar0 + 8 * B_WR, 1);
            fence_async();
            mbar_expect_tx(rbar, 8192);
            if (q == 3) {
                mbar_expect_tx(bar0 + 8 * B_WR, 2048);
                bulk_g2s(sb + OFF_GP, p.wr, 2048, bar0 + 8 * B_WR);
            }
        }
        __syncwarp();
        cluster_arrive();
        wait_until(t0 + ROW_DELAY + q * ROW_PERIOD);
        if (one) {
            tma_load_3d(sb + OFF_ROWS + 8192 * q, &maps.rows, 16 * b, 4 * q, rbar);
            asm volatile("prefetch.tensormap [%0];" ::"l"(&maps.u + q) : "memory");
        }
        __syncwarp();
        cluster_wait();
        if (END_BAR) cluster_arrive();
        STAMP(1);
        wait_until(t0 + X_DELAY + q * X_PERIOD);
        if (one) tma_load_4d_both(sb + OFF_X + 8192 * (4 * h + q), &maps.u, 16 * cl, 4 * (4 * h + q), bar0 + 8 * (B_X + 4 * h + q));
        STAMP(2);
        const char* src = (const char*)((b >> 6) ? p.wu : p.wg) + (64 * q + (b & 63)) * 7168 + 128 * lane;
        const uint32_t phase = t0 + PF_START + (b * PF_PERIOD >> 7) + q * PF_PERIOD;
        auto fill = [&](int j, uint32_t due, const CUtensorMap* map, int c0, int c3) {
            const uint32_t bar = bar0 + 8 * (B_FULL + q + 4 * (j & 1));
            wait_until(due);
            mbar_wait_bounded(bar + 8 * (B_EMPTY - B_FULL), (j >> 1) & 1);
            if (one) {
                mbar_expect_tx(bar, 8192);
                tma_load_4d(sb + OFF_RING + (q + 4 * (j & 1)) * 8192, map, c0, c3, bar);
            }
            STAMP(3 + (j >> 1));
        };
#pragma unroll 1
        for (int j = 0; j < 4; j++) {
            wait_until(phase + 4 * j * PF_PERIOD);
            asm volatile("prefetch.global.L2 [%0];" ::"l"(src) : "memory");
            if (lane < 24) asm volatile("prefetch.global.L2 [%0];" ::"l"(src + 4096) : "memory");
            src += 256 * 7168;
            STAMP(6);
            if (b < GU_CTAS) fill(j, t0 + LD_START + (b * PHG >> 7) + (q + 4 * j) * LD_PERIOD, &maps.wgu, 32 * b, q + 4 * j);
        }
#pragma unroll 1
        for (int j = 4; j < (q < 3 ? 6 : 5); j++)
            fill(j, phase + 4 * j * PF_PERIOD + (q + 4 * j - 16) * WD_EXTRA, &maps.wd, 64 * (b >> 3), 7 * (b & 7) + q + 4 * j - 16);
        if (PAD) {
            float x = __uint_as_float(t0);
#pragma unroll
            for (int i = 0; i < PAD; i++) asm volatile("fma.rn.f32 %0, %0, %0, %0;" : "+f"(x));
            sts32(sb + OFF_MISC + 16 + 4 * q, __float_as_uint(x));
        }
        if (q >= 2) mbar_wait_bounded(bar0 + 8 * (B_DONE - 2 + q), 0);
    }
    if (END_BAR) cluster_wait();
}

typedef CUresult (*EncodeFn)(CUtensorMap*, CUtensorMapDataType, cuuint32_t, void*, const cuuint64_t*, const cuuint64_t*,
                             const cuuint32_t*, const cuuint32_t*, CUtensorMapInterleave, CUtensorMapSwizzle,
                             CUtensorMapL2promotion, CUtensorMapFloatOOBfill);

void make_map(EncodeFn enc, CUtensorMap* m, int rank, const void* ptr, const cuuint64_t (&dims)[5], const cuuint64_t (&str)[4],
              const cuuint32_t (&box)[5], CUtensorMapSwizzle sw, CUtensorMapL2promotion pr) {
    const cuuint32_t es[5] = {1, 1, 1, 1, 1};
    CUresult rc = enc(m, CU_TENSOR_MAP_DATA_TYPE_BFLOAT16, rank, const_cast<void*>(ptr), dims, str, box, es, CU_TENSOR_MAP_INTERLEAVE_NONE, sw, pr,
                      CU_TENSOR_MAP_FLOAT_OOB_FILL_NONE);
    (void)rc;
}

}

extern "C" void kernel_launch(void* const* d_in, const int* in_sizes, int n_in, void* d_out, int out_size) {
    (void)in_sizes; (void)n_in; (void)out_size;
    static EncodeFn enc = nullptr;
    static void* scr = nullptr;
    if (!enc) {
        void* fn = nullptr;
        cudaDriverEntryPointQueryResult q;
        cudaGetDriverEntryPoint("cuTensorMapEncodeTiled", &fn, cudaEnableDefault, &q);
        enc = (EncodeFn)fn;
        cudaGetSymbolAddress(&scr, g_scr);
        cudaFuncSetAttribute(fused_kernel, cudaFuncAttributeMaxDynamicSharedMemorySize, SMEM_BYTES);
    }
    Maps maps;
    const uintptr_t ag = (uintptr_t)d_in[9], au = (uintptr_t)d_in[10];
    const auto noprom = CU_TENSOR_MAP_L2_PROMOTION_NONE, prom = CU_TENSOR_MAP_L2_PROMOTION_L2_128B;
    make_map(enc, &maps.rows, 3, d_in[0], {64, SEQ, 16, 1}, {2048, 128, 0}, {64, 16, 4, 1}, CU_TENSOR_MAP_SWIZZLE_128B, noprom);
    make_map(enc, &maps.u, 4, d_in[0], {DM, 4, 16, 32}, {32768, 2048, 131072}, {16, 4, 16, 4}, CU_TENSOR_MAP_SWIZZLE_32B, (CUtensorMapL2promotion)XPROM);
    make_map(enc, &maps.out, 5, d_out, {DM, 4, 8, 2, 32}, {32768, 2048, 16384, 131072}, {16, 4, 2, 2, 4}, CU_TENSOR_MAP_SWIZZLE_NONE, noprom);
    make_map(enc, &maps.wgu, 4, (const void*)(ag < au ? ag : au), {FF, 64, 2, 16}, {FF * 2, ag < au ? au - ag : ag - au, 64 * FF * 2}, {32, 64, 2, 1},
             CU_TENSOR_MAP_SWIZZLE_64B, prom);
    make_map(enc, &maps.wd, 4, d_in[11], {DM, 64, 1, 56}, {2048, 131072, 131072}, {64, 64, 1, 1}, CU_TENSOR_MAP_SWIZZLE_128B, prom);
    Ptrs p;
    p.u = (const __nv_bfloat16*)d_in[0];
    p.logA = (const __nv_bfloat16*)d_in[1];
    p.Aim = (const __nv_bfloat16*)d_in[2];
    p.Cre = (const __nv_bfloat16*)d_in[3];
    p.Cim = (const __nv_bfloat16*)d_in[4];
    p.ldt = (const __nv_bfloat16*)d_in[5];
    p.dsk = (const __nv_bfloat16*)d_in[6];
    p.wr = (const __nv_bfloat16*)d_in[8];
    p.wg = (const __nv_bfloat16*)d_in[9];
    p.wu = (const __nv_bfloat16*)d_in[10];
    p.out = (__nv_bfloat16*)d_out;
    p.scr = (uint32_t*)scr;
    p.up_first = ag < au ? 0 : 4096;
    p.zero = 0;
    fused_kernel<<<NCTA + 2, NTHR, SMEM_BYTES, cudaStreamPerThread>>>(p, maps);
}
```

```cpp
#include <cuda_runtime.h>
#include <cuda_bf16.h>
#include <cuda_fp16.h>
#include <cuda.h>
#include <stdint.h>

namespace {

constexpr int SEQ = 2048, DM = 1024, NMODE = 128, FF = 3584;
constexpr int NCTA = 128, NTHR = 512;
constexpr int GU_CTAS = 112;

constexpr int OFF_X = 0;
constexpr int OFF_RING = 65536;
constexpr int ROW_PITCH = 2064;
constexpr int OFF_ROWS = OFF_RING + 32768;
constexpr int OFF_XS = OFF_RING + 65536;
constexpr int OFF_PRIV = OFF_XS + 8 * ROW_PITCH;
constexpr int PRIV = 8768;
constexpr int PLANE = 2240;
constexpr int OFF_GP = OFF_PRIV + 8 * PRIV;
constexpr int OFF_LC = OFF_GP + 8192;
constexpr int OFF_BAR = OFF_LC + 2048;
constexpr int OFF_MISC = OFF_BAR + 352;
constexpr int OFF_STAMP = OFF_MISC + 288;
constexpr int SMEM_BYTES = OFF_STAMP;

constexpr int B_X = 0, B_FULL = 8, B_EMPTY = 16, B_RECV = 24, B_XS = 28, B_DONE = 29, B_ST = 30, B_ROW = 32, B_WR = 36, B_KG = 37, B_VT = 38, B_PV = 39;

constexpr int T_DENSE = 4416;
constexpr int T_PATCH = T_DENSE + 2176;
constexpr int T_S4 = T_PATCH + 112;
constexpr int T_S8 = T_S4 + 736;
constexpr int REC = 272;

constexpr uint32_t SPIN_LIMIT = 1u << 22;
constexpr int CONV_REGS = 168, FFN_REGS = 144, PROD_REGS = 32;
#define NPRE 4

#define ROW_DELAY 400
#define ROW_PERIOD 560
#define X_DELAY 2500
#define PF_START 3400
#define PF_PERIOD 525
#define WD_EXTRA 110
#define LD_START 5500
#define LD_LAG 520
constexpr int LD_PERIOD = (PF_START + 16 * PF_PERIOD + LD_LAG - LD_START) / 15, LD_SPREAD = 480;

constexpr int S_STAT = 0;
constexpr int S_KEY = S_STAT + 8192;
constexpr int S_SEL = S_KEY + 2048;
constexpr int S_EPOCH = S_SEL + 128;
constexpr int S_H = S_EPOCH + 32;
constexpr int S_Y = S_H + 2 * GU_CTAS * 128;
constexpr int S_END = S_Y + 64 * 1024;
__device__ __align__(1024) uint32_t g_scr[S_END];

struct Ptrs {
    const __nv_bfloat16 *logA, *Aim, *Cre, *Cim, *ldt, *dsk, *u, *wr;
    uint32_t* scr;
    const __nv_bfloat16 *wg, *wu;
    __nv_bfloat16* out;
    uint32_t up_first;
    uint32_t zero;
};
struct Maps {
    CUtensorMap rows, u, out, wgu, wd;
};

__device__ __forceinline__ uint32_t clk() { uint32_t c; asm volatile("mov.u32 %0, %%clock;" : "=r"(c)); return c; }
#define STAMP(i) do { } while (0)
#define GSTAMP(i) do { } while (0)

template <int N> struct IC { static constexpr int value = N; };

__device__ __forceinline__ uint32_t s_u32(const void* p) { return (uint32_t)__cvta_generic_to_shared(p); }
__device__ __forceinline__ void mbar_init(uint32_t b, uint32_t n) {
    asm volatile("mbarrier.init.shared::cta.b64 [%0], %1;" ::"r"(b), "r"(n) : "memory");
}
__device__ __forceinline__ void mbar_expect_tx(uint32_t b, uint32_t bytes) {
    asm volatile("mbarrier.arrive.expect_tx.shared::cta.b64 _, [%0], %1;" ::"r"(b), "r"(bytes) : "memory");
}
__device__ __forceinline__ void mbar_arrive(uint32_t b) {
    asm volatile("mbarrier.arrive.shared::cta.b64 _, [%0];" ::"r"(b) : "memory");
}
__device__ __forceinline__ void mbar_arrive_peer(uint32_t b_cluster) {
    asm volatile("mbarrier.arrive.relaxed.cluster.shared::cluster.b64 _, [%0];" ::"r"(b_cluster) : "memory");
}
__device__ __forceinline__ void mbar_wait(uint32_t b, uint32_t parity) {
    asm volatile("{\n\t.reg .pred p;\nW:\n\tmbarrier.try_wait.parity.shared::cta.b64 p, [%0], %1;\n\t@!p bra W;\n\t}" ::"r"(b), "r"(parity) : "memory");
}
__device__ __forceinline__ void mbar_wait_bounded(uint32_t b, uint32_t parity) {
    asm volatile("{\n\t.reg .pred p;\n\t.reg .u32 c;\n\tmov.u32 c, 0;\n"
                 "W:\n\tmbarrier.try_wait.parity.shared::cta.b64 p, [%0], %1, 4000;\n\t@p bra D;\n\t"
                 "add.u32 c, c, 1;\n\tsetp.lt.u32 p, c, 1048576;\n\t@p bra W;\n\ttrap;\nD:\n\t}"
                 ::"r"(b), "r"(parity) : "memory");
}
__device__ __forceinline__ bool elect_one() {
    uint32_t p;
    asm volatile("{ .reg .pred P; elect.sync _|P, 0xffffffff; selp.u32 %0, 1, 0, P; }" : "=r"(p));
    return p != 0;
}
__device__ __forceinline__ uint32_t mapa(uint32_t a, uint32_t rank) {
    uint32_t r;
    asm("mapa.shared::cluster.u32 %0, %1, %2;" : "=r"(r) : "r"(a), "r"(rank));
    return r;
}
__device__ __forceinline__ void cluster_arrive() { asm volatile("barrier.cluster.arrive.relaxed.aligned;" ::: "memory"); }
__device__ __forceinline__ void cluster_wait() { asm volatile("barrier.cluster.wait.aligned;" ::: "memory"); }
__device__ __forceinline__ void tma_load_3d(uint32_t dst, const CUtensorMap* m, int c1, int c2, uint32_t bar) {
    asm volatile("cp.async.bulk.tensor.3d.shared::cluster.global.mbarrier::complete_tx::bytes [%0], [%1, {%3, %4, %5}], [%2];"
                 ::"r"(dst), "l"(m), "r"(bar), "r"(0), "r"(c1), "r"(c2) : "memory");
}
__device__ __forceinline__ void tma_load_4d(uint32_t dst, const CUtensorMap* m, int c0, int c3, uint32_t bar) {
    uint64_t pol;
    asm("createpolicy.fractional.L2::evict_first.b64 %0, 1.0;" : "=l"(pol));
    asm volatile("cp.async.bulk.tensor.4d.shared::cluster.global.mbarrier::complete_tx::bytes.L2::cache_hint [%0], [%1, {%3, %5, %5, %4}], [%2], %6;"
                 ::"r"(dst), "l"(m), "r"(bar), "r"(c0), "r"(c3), "r"(0), "l"(pol) : "memory");
}
__device__ __forceinline__ void wait_until(uint32_t t) {
    asm volatile("{\n\t.reg .pred p;\n\t.reg .s32 c;\nW:\n\tmov.u32 c, %%clock;\n\tsub.s32 c, %0, c;\n\tshr.s32 c, c, 2;\n\tsetp.gt.s32 p, c, 63;\n\t"
                 "@p nanosleep.u32 c;\n\t@p bra.uni W;\n\t}" ::"r"(t) : "memory");
}
__device__ __forceinline__ void tma_load_4d_both(uint32_t dst, const CUtensorMap* m, int c0, int c3, uint32_t bar) {
    asm volatile("cp.async.bulk.tensor.4d.shared::cluster.global.mbarrier::complete_tx::bytes.multicast::cluster [%0], [%1, {%3, %6, %6, %4}], [%2], %5;"
                 ::"r"(dst), "l"(m), "r"(bar), "r"(c0), "r"(c3), "h"((uint16_t)3), "r"(0) : "memory");
}
__device__ __forceinline__ void bulk_g2s(uint32_t dst, const void* src, uint32_t bytes, uint32_t bar) {
    asm volatile("cp.async.bulk.shared::cluster.global.mbarrier::complete_tx::bytes [%0], [%1], %2, [%3];"
                 ::"r"(dst), "l"(src), "r"(bytes), "r"(bar) : "memory");
}
__device__ __forceinline__ void fence_async() { asm volatile("fence.proxy.async.shared::cta;" ::: "memory"); }
__device__ __forceinline__ void named_sync(int id, int n) { asm volatile("bar.sync %0, %1;" ::"r"(id), "r"(n) : "memory"); }

__device__ __forceinline__ void ldsm4(uint32_t* r, uint32_t a) {
    asm volatile("ldmatrix.sync.aligned.m8n8.x4.shared.b16 {%0,%1,%2,%3}, [%4];"
                 : "=r"(r[0]), "=r"(r[1]), "=r"(r[2]), "=r"(r[3]) : "r"(a));
}
__device__ __forceinline__ void ldsm4t(uint32_t* r, uint32_t a) {
    asm volatile("ldmatrix.sync.aligned.m8n8.x4.trans.shared.b16 {%0,%1,%2,%3}, [%4];"
                 : "=r"(r[0]), "=r"(r[1]), "=r"(r[2]), "=r"(r[3]) : "r"(a));
}
__device__ __forceinline__ void stsm4t(uint32_t a, const uint32_t* r) {
    asm volatile("stmatrix.sync.aligned.m8n8.x4.trans.shared.b16 [%0], {%1,%2,%3,%4};"
                 ::"r"(a), "r"(r[0]), "r"(r[1]), "r"(r[2]), "r"(r[3]) : "memory");
}
__device__ __forceinline__ uint32_t lds32(uint32_t a) { uint32_t v; asm volatile("ld.shared.u32 %0, [%1];" : "=r"(v) : "r"(a)); return v; }
__device__ __forceinline__ uint32_t lds32v(uint32_t a) { uint32_t v; asm volatile("ld.volatile.shared.u32 %0, [%1];" : "=r"(v) : "r"(a)); return v; }
__device__ __forceinline__ uint2 lds64(uint32_t a) { uint2 v; asm volatile("ld.shared.v2.u32 {%0,%1}, [%2];" : "=r"(v.x), "=r"(v.y) : "r"(a)); return v; }
__device__ __forceinline__ uint4 lds128(uint32_t a) {
    uint4 v; asm volatile("ld.shared.v4.u32 {%0,%1,%2,%3}, [%4];" : "=r"(v.x), "=r"(v.y), "=r"(v.z), "=r"(v.w) : "r"(a)); return v;
}
template <int D> __device__ __forceinline__ void sts16x2(uint32_t a, float x) {
    asm volatile("{ .reg .b16 h; cvt.rn.bf16.f32 h, %1; st.shared.b16 [%0], h; st.shared.b16 [%0 + %2], h; }" ::"r"(a), "f"(x), "n"(D) : "memory");
}
__device__ __forceinline__ void sts32(uint32_t a, uint32_t v) { asm volatile("st.shared.u32 [%0], %1;" ::"r"(a), "r"(v) : "memory"); }
__device__ __forceinline__ void sts64(uint32_t a, uint32_t x, uint32_t y) { asm volatile("st.shared.v2.u32 [%0], {%1,%2};" ::"r"(a), "r"(x), "r"(y) : "memory"); }
__device__ __forceinline__ void sts128(uint32_t a, uint32_t x, uint32_t y, uint32_t z, uint32_t w) {
    asm volatile("st.shared.v4.u32 [%0], {%1,%2,%3,%4};" ::"r"(a), "r"(x), "r"(y), "r"(z), "r"(w) : "memory");
}
__device__ __forceinline__ void sts128f(uint32_t a, const float* c) {
    asm volatile("st.shared.v4.f32 [%0], {%1,%2,%3,%4};" ::"r"(a), "f"(c[0]), "f"(c[1]), "f"(c[2]), "f"(c[3]) : "memory");
}
__device__ __forceinline__ uint2 ldg64(const void* p) {
    uint2 v; asm volatile("ld.global.nc.L1::no_allocate.v2.u32 {%0,%1}, [%2];" : "=r"(v.x), "=r"(v.y) : "l"(p)); return v;
}
__device__ __forceinline__ uint32_t ldg16(const void* p) {
    uint16_t v; asm volatile("ld.global.nc.u16 %0, [%1];" : "=h"(v) : "l"(p)); return v;
}
__device__ __forceinline__ uint32_t ld_relaxed_32(const void* p) {
    uint32_t v; asm volatile("ld.relaxed.gpu.global.u32 %0, [%1];" : "=r"(v) : "l"(p) : "memory"); return v;
}
__device__ __forceinline__ uint2 ld_relaxed_64(const void* p) {
    unsigned long long v;
    asm volatile("ld.relaxed.gpu.global.u64 %0, [%1];" : "=l"(v) : "l"(p) : "memory");
    return make_uint2((uint32_t)v, (uint32_t)(v >> 32));
}
__device__ __forceinline__ uint4 ld_relaxed_128(const void* p) {
    uint4 v; asm volatile("ld.relaxed.gpu.global.v4.u32 {%0,%1,%2,%3}, [%4];" : "=r"(v.x), "=r"(v.y), "=r"(v.z), "=r"(v.w) : "l"(p) : "memory"); return v;
}
__device__ __forceinline__ void st_relaxed_32(void* p, uint32_t v) {
    asm volatile("st.relaxed.gpu.global.u32 [%0], %1;" ::"l"(p), "r"(v) : "memory");
}
__device__ __forceinline__ void st_relaxed_128(void* p, uint32_t x, uint32_t y, uint32_t z, uint32_t w) {
    asm volatile("st.relaxed.gpu.global.v4.u32 [%0], {%1,%2,%3,%4};" ::"l"(p), "r"(x), "r"(y), "r"(z), "r"(w) : "memory");
}
__device__ __forceinline__ void st_relaxed_64(void* p, uint32_t x, uint32_t y) {
    asm volatile("st.relaxed.gpu.global.u64 [%0], %1;" ::"l"(p), "l"((unsigned long long)x | ((unsigned long long)y << 32)) : "memory");
}
__device__ __forceinline__ void mma_bf16(float* c, uint32_t a0, uint32_t a1, uint32_t a2, uint32_t a3, uint32_t b0, uint32_t b1) {
    asm("mma.sync.aligned.m16n8k16.row.col.f32.bf16.bf16.f32 {%0,%1,%2,%3}, {%4,%5,%6,%7}, {%8,%9}, {%0,%1,%2,%3};"
                 : "+f"(c[0]), "+f"(c[1]), "+f"(c[2]), "+f"(c[3]) : "r"(a0), "r"(a1), "r"(a2), "r"(a3), "r"(b0), "r"(b1));
}
__device__ __forceinline__ void mma_bf16v(float* c, const uint32_t* a, uint32_t b0, uint32_t b1) {
    asm volatile("mma.sync.aligned.m16n8k16.row.col.f32.bf16.bf16.f32 {%0,%1,%2,%3}, {%4,%5,%6,%7}, {%8,%9}, {%0,%1,%2,%3};"
                 : "+f"(c[0]), "+f"(c[1]), "+f"(c[2]), "+f"(c[3]) : "r"(a[0]), "r"(a[1]), "r"(a[2]), "r"(a[3]), "r"(b0), "r"(b1));
}
__device__ __forceinline__ void mma_bf16_z(float* c, uint32_t a0, uint32_t a1, uint32_t a2, uint32_t a3, uint32_t b0, uint32_t b1) {
    asm("mma.sync.aligned.m16n8k16.row.col.f32.bf16.bf16.f32 {%0,%1,%2,%3}, {%4,%5,%6,%7}, {%8,%9}, {%10,%10,%10,%10};"
        : "=f"(c[0]), "=f"(c[1]), "=f"(c[2]), "=f"(c[3]) : "r"(a0), "r"(a1), "r"(a2), "r"(a3), "r"(b0), "r"(b1), "f"(0.f));
}
__device__ __forceinline__ void mma_f16(float* c, const uint4& a, uint32_t b0, uint32_t b1) {
    asm("mma.sync.aligned.m16n8k16.row.col.f32.f16.f16.f32 {%0,%1,%2,%3}, {%4,%5,%6,%7}, {%8,%9}, {%0,%1,%2,%3};"
                 : "+f"(c[0]), "+f"(c[1]), "+f"(c[2]), "+f"(c[3]) : "r"(a.x), "r"(a.y), "r"(a.z), "r"(a.w), "r"(b0), "r"(b1));
}
__device__ __forceinline__ uint32_t pack_bf16(float lo, float hi) {
    uint32_t r; asm("cvt.rn.bf16x2.f32 %0, %1, %2;" : "=r"(r) : "f"(hi), "f"(lo)); return r;
}
__device__ __forceinline__ uint32_t pack_bf16v(float lo, float hi) {
    uint32_t r; asm("cvt.rn.satfinite.bf16x2.f32 %0, %1, %2;" : "=r"(r) : "f"(hi), "f"(lo)); return r;
}
__device__ __forceinline__ uint32_t pack_f16(float lo, float hi) {
    uint32_t r; asm("cvt.rn.f16x2.f32 %0, %1, %2;" : "=r"(r) : "f"(hi), "f"(lo)); return r;
}
__device__ __forceinline__ float bf_lo(uint32_t v) { return __uint_as_float(v << 16); }
__device__ __forceinline__ float bf_hi(uint32_t v) { return __uint_as_float(v & 0xffff0000u); }
__device__ __forceinline__ float bf_round(float x) { return __uint_as_float(pack_bf16(0.f, x)); }
__device__ __forceinline__ __nv_bfloat162 as_b2(uint32_t x) { return *reinterpret_cast<__nv_bfloat162*>(&x); }
__device__ __forceinline__ uint32_t as_u(__nv_bfloat162 x) { return *reinterpret_cast<uint32_t*>(&x); }
__device__ __forceinline__ uint32_t badd2(uint32_t a, uint32_t b) { uint32_t r; asm("add.rn.bf16x2 %0, %1, %2;" : "=r"(r) : "r"(a), "r"(b)); return r; }
__device__ __forceinline__ float rcpf(float x) { float r; asm("rcp.approx.ftz.f32 %0, %1;" : "=f"(r) : "f"(x)); return r; }
__device__ __forceinline__ float sqrtaf(float x) { float r; asm("sqrt.approx.ftz.f32 %0, %1;" : "=f"(r) : "f"(x)); return r; }
__device__ __forceinline__ float ex2f(float x) { float r; asm("ex2.approx.ftz.f32 %0, %1;" : "=f"(r) : "f"(x)); return r; }
constexpr float L2E = 1.4426950408889634f;
constexpr uint32_t ONES = 0x3f803f80u;

__device__ __forceinline__ uint2 recip2(uint32_t s2) {
    const uint32_t hi = pack_bf16(rcpf(bf_lo(s2)), rcpf(bf_hi(s2)));
    return make_uint2(hi, as_u(__hmul2(__hfma2(__hneg2(as_b2(s2)), as_b2(hi), as_b2(ONES)), as_b2(hi))));
}
__device__ __forceinline__ uint32_t normalize2(uint32_t x, __nv_bfloat162 m, __nv_bfloat162 rh, __nv_bfloat162 rl) {
    const __nv_bfloat162 d = __hsub2(as_b2(x), m);
    return as_u(__hfma2(d, rh, __hmul2(d, rl)));
}

__device__ __forceinline__ uint32_t unorder_key(uint32_t k16) { return k16 ^ ((k16 & 0x8000u) ? 0x8000u : 0xffffu); }

struct cplx { float r, i; };
__device__ __forceinline__ cplx csq(cplx a) { return {a.r * a.r - a.i * a.i, (a.r + a.r) * a.i}; }
__device__ __forceinline__ cplx csq_conj(cplx a) { return {a.r * a.r - a.i * a.i, (-a.r - a.r) * a.i}; }
__device__ __forceinline__ cplx cexpp(float a2, float th) {
    float m = ex2f(a2), s, c;
    __sincosf(th, &s, &c);
    return {m * c, m * s};
}
struct hc { __half2 r, i; };
__device__ __forceinline__ __half2 as_h2(uint32_t x) { return *reinterpret_cast<__half2*>(&x); }
__device__ __forceinline__ uint32_t as_u(__half2 x) { return *reinterpret_cast<uint32_t*>(&x); }
__device__ __forceinline__ hc hmul(hc a, hc b) {
    return {__hfma2(a.r, b.r, __hneg2(__hmul2(a.i, b.i))), __hfma2(a.r, b.i, __hmul2(a.i, b.r))};
}
__device__ __forceinline__ hc hpack(cplx a, cplx b) { return {as_h2(pack_f16(a.r, b.r)), as_h2(pack_f16(a.i, b.i))}; }
__device__ __forceinline__ void st_pair(uint32_t a, hc x, hc y) { sts128(a, as_u(x.r), as_u(x.i), as_u(y.r), as_u(y.i)); }
__device__ __forceinline__ void st_quad(uint32_t a, hc x, hc y) { sts128(a, as_u(x.r), as_u(y.r), as_u(x.i), as_u(y.i)); }

#define KSTAMP(i, dep) do { } while (0)
__device__ __forceinline__ void kgen_mma(float (&acc)[5][4], uint32_t priv, int lane, uint2 la, uint2 aim, uint2 cre, uint2 cim, float dt, uint32_t cs2) {
    const int g = lane >> 2, t = lane & 3;
#pragma unroll
    for (int i = 0; i < 5; i++) { acc[i][0] = acc[i][1] = acc[i][2] = acc[i][3] = 0.f; }
    const uint32_t wr = priv + lane * REC, rd = priv + 2 * t * REC;
    const float ndl = -dt * L2E;
#pragma unroll 1
    for (int ps = 0; ps < 2; ps++) {
        const uint32_t lw = ps ? la.y : la.x, iw = ps ? aim.y : aim.x;
        const uint32_t crw = as_u(__hmul2(as_b2(ps ? cre.y : cre.x), as_b2(cs2))), ciw = as_u(__hmul2(as_b2(ps ? cim.y : cim.x), as_b2(cs2)));
        const uint32_t ap = pack_bf16(ex2f(bf_lo(lw) * L2E), ex2f(bf_hi(lw) * L2E));
        const float a2[2] = {bf_lo(ap) * ndl, bf_hi(ap) * ndl}, th[2] = {bf_lo(iw) * dt, bf_hi(iw) * dt};
        cplx p1[2], p2[2], p4[2], p8[2], p32[2], p64[2], p128[2], p256[2], p512[2];
#pragma unroll
        for (int i = 0; i < 2; i++) {
            p1[i] = cexpp(a2[i], th[i]); p32[i] = cexpp(a2[i] * 32.f, th[i] * -32.f);
            p2[i] = csq(p1[i]); p4[i] = csq(p2[i]); p8[i] = csq_conj(p4[i]);
            p64[i] = csq(p32[i]); p128[i] = csq_conj(p64[i]); p256[i] = csq(p128[i]); p512[i] = csq(p256[i]);
        }
        const hc C = {as_h2(pack_f16(bf_lo(crw), bf_hi(crw))), as_h2(pack_f16(bf_lo(ciw), bf_hi(ciw)))};
        const hc z1 = hpack(p1[0], p1[1]), z2 = hpack(p2[0], p2[1]), z4 = hpack(p4[0], p4[1]);
        const hc y8 = hpack(p8[0], p8[1]), y32 = hpack(p32[0], p32[1]), y64 = hpack(p64[0], p64[1]);
        const hc z128 = hpack(p128[0], p128[1]), z256 = hpack(p256[0], p256[1]), z512 = hpack(p512[0], p512[1]);
        KSTAMP(8 + 3 * ps, z512.r);
        __syncwarp();
        const hc c1 = hmul(C, z1), c2 = hmul(C, z2), c5 = hmul(c1, z4), c6 = hmul(c2, z4);
        st_pair(wr + 160, hmul(c1, z128), hmul(c2, z128));
        st_pair(wr + 128, c1, c2);
        st_pair(wr + 176, hmul(c5, z128), hmul(c6, z128));
        st_pair(wr + 144, c5, c6);
        const hc y16 = hmul(y8, y8), y48 = hmul(y16, y32), y24 = hmul(y16, y8), y40 = hmul(y32, y8), y56 = hmul(y48, y8), y72 = hmul(y64, y8);
        st_quad(wr, {as_h2(0x3c003c00u), as_h2(0u)}, y8);
        st_quad(wr + 80, hmul(y64, y16), hmul(y64, y24));
        st_quad(wr + 16, y16, y24);
        st_quad(wr + 96, hmul(y64, y32), hmul(y64, y40));
        st_quad(wr + 32, y32, y40);
        st_quad(wr + 112, hmul(y64, y48), hmul(y64, y56));
        st_quad(wr + 48, y48, y56);
        st_quad(wr + 64, y64, y72);
        const hc z258 = hmul(z256, z2);
        st_pair(wr + 192, hmul(z256, z1), z258);
        st_pair(wr + 224, z2, hmul(z512, z4));
        st_pair(wr + 240, z2, hmul(z512, z512));
        st_pair(wr + 208, z258, z512);
        KSTAMP(9 + 3 * ps, z512.r);
        __syncwarp();
#pragma unroll
        for (int k2 = 0; k2 < 4; k2++) {
#pragma unroll
            for (int s = 0; s < 2; s++) {
                const uint32_t o = rd + k2 * 8 * REC + s * REC;
                const uint4 A = lds128(o + 16 * g);
                const uint2 h = lds64(o + 128 + 8 * g);
                const uint4 M = lds128(o + 192 + 16 * (g & 1)), N = lds128(o + 224 + 8 * (g & 2));
                const hc H0 = {as_h2(h.x), as_h2(h.y)};
                const hc H1 = hmul(H0, {as_h2(N.x), as_h2(N.y)}), H2 = hmul(H0, {as_h2(M.x), as_h2(M.y)});
                const hc H3 = hmul(H2, {as_h2(M.z), as_h2(M.w)}), H4 = hmul(H3, {as_h2(N.z), as_h2(N.w)});
                mma_f16(acc[0], A, h.x, h.y);
                mma_f16(acc[1], A, as_u(H1.r), as_u(H1.i));
                mma_f16(acc[2], A, as_u(H2.r), as_u(H2.i));
                mma_f16(acc[3], A, as_u(H3.r), as_u(H3.i));
                mma_f16(acc[4], A, as_u(H4.r), as_u(H4.i));
            }
        }
        KSTAMP(10 + 3 * ps, z512.r);
    }
}

__device__ __forceinline__ void kgen_tables(const float (&acc)[5][4], uint32_t priv, int lane, float scale, float k0) {
    const int g = lane >> 2, t0 = lane & 1, t1 = (lane >> 1) & 1;
    __syncwarp();
    sts128(priv + 16 * lane + (lane < 17 ? T_PATCH - 48 : T_S4 + 608 - 272), 0, 0, 0, 0);
    if (lane < 20) sts128(priv + 16 * lane + (lane < 8 ? 0 : lane < 16 ? PLANE - 128 : T_DENSE - 256), 0, 0, 0, 0);
    uint32_t w2[2], w3[2], w4[2], ab[2], W[2], pv[2];
#pragma unroll
    for (int hf = 0; hf < 2; hf++) {
        const float k1 = acc[0][2 * hf] * scale, k2 = acc[0][2 * hf + 1] * scale, k3 = acc[1][2 * hf] * scale, k4 = acc[1][2 * hf + 1] * scale;
        w2[hf] = pack_bf16(k2, k1); w3[hf] = pack_bf16(k3, k2); w4[hf] = pack_bf16(k4, k3);
        ab[hf] = pack_bf16(acc[2][2 * hf + 1] * scale, acc[2][2 * hf] * scale);
        W[hf] = __byte_perm(w4[hf], ab[hf], 0x5410);
    }
    pv[1] = __shfl_xor_sync(0xffffffffu, t0 ? W[0] : W[1], 1);
    pv[0] = __shfl_sync(0xffffffffu, t0 ? W[1] : W[0], t0 ? lane - 1 : lane < 4 ? 31 - lane : lane - 3);
    const uint32_t kk = pack_bf16(k0, 0.f);
    if (lane == 0) pv[0] = __byte_perm(kk, pv[0], 0x5410);
    const uint32_t pd = priv + T_DENSE + 64 + 512 * t1 + 64 * g + 16 * t0;
#pragma unroll
    for (int hf = 0; hf < 2; hf++) {
        sts128(pd + 32 * hf, __byte_perm(w2[hf], pv[hf], 0x5432), w2[hf], w3[hf], w4[hf]);
        sts128(pd + 32 * hf + 1024, __byte_perm(pv[hf], 0, 0x3232), __byte_perm(ab[hf], pv[hf], 0x7632), ab[hf], __byte_perm(ab[hf], 0, 0x1010));
    }
    __syncwarp();
    if (lane == 31) {
        const uint32_t aa = __byte_perm(ab[1], 0, 0x1010);
        sts32(priv + T_DENSE + 60, kk);
        sts128(priv + T_PATCH - 64, aa, aa, aa << 16, 0u);
    }
}
__device__ __forceinline__ void kgen_tables2(const float (&acc)[5][4], uint32_t priv, int lane, float scale) {
    const int g = lane >> 2, t0 = lane & 1, t1 = (lane >> 1) & 1;
    const uint32_t p4 = priv + T_S4 + 16 * (6 + g + 8 * t1) + 4 * (t0 ^ 1), p8 = priv + T_S8 + 8 * (6 + g + 8 * t1 + 32 * t0);
#pragma unroll
    for (int i = 0; i < 4; i++) {
        sts16x2<18>(p4 + 256 * (i & 1) + 8 * (i >> 1), acc[3][i] * scale);
        sts16x2<10>(p8 + 128 * (i & 1) + 4 * (i >> 1), acc[4][i] * scale);
    }
    if (lane == 31) {
        const uint32_t c3 = pack_bf16(acc[3][3] * scale, 0.f);
        sts128(priv + T_PATCH + 48, c3, c3 * 0x10001u, c3 << 16, 0u);
    }
    __syncwarp();
}

__device__ __forceinline__ void ld_frag(uint32_t (&T)[4], uint32_t q) { T[0] = lds32(q); T[1] = lds32(q + 32); T[2] = lds32(q - 32); T[3] = lds32v(q); }
__device__ __forceinline__ void ld_swap(uint32_t (&T)[4], uint32_t q) { T[2] = lds32v(q); T[3] = lds32v(q + 32); T[0] = lds32v(q - 32); T[1] = lds32v(q); }
__device__ __forceinline__ void add_frag(uint32_t (&S)[4], const uint32_t (&E)[4], const uint32_t (&O)[4]) {
    S[0] = badd2(E[0], O[1]); S[1] = badd2(E[1], O[3]); S[2] = badd2(E[2], O[0]); S[3] = badd2(E[3], O[2]);
}
__device__ __forceinline__ void mma4(float* c, const uint32_t (&a)[4], uint32_t b0, uint32_t b1, bool first = false) {
    if (first) mma_bf16_z(c, a[0], a[1], a[2], a[3], b0, b1);
    else mma_bf16(c, a[0], a[1], a[2], a[3], b0, b1);
}
template <bool FIRST>
__device__ __forceinline__ void dense_step(float (&acc)[16][4], float (&B)[8][4], uint32_t (&T0)[4], uint32_t (&T1)[4], uint32_t (&R)[8][4],
                                           uint32_t pq, uint32_t va) {
    uint32_t T2[4], T3[4], S[4], s[8][2];
#pragma unroll
    for (int i = NPRE; i < 8; i++) ldsm4(R[i], va + i * 256);
    ld_frag(T2, pq + 1024); ld_swap(T3, pq + 1536);
    add_frag(S, T0, T1);
#pragma unroll
    for (int i = 0; i < 8; i++) {
        s[i][0] = badd2(R[i][0], R[i][3]); s[i][1] = badd2(R[i][1], R[i][2]);
        mma4(acc[2 * i], T0, R[i][0], R[i][1], FIRST);
        mma4(B[i], T1, R[i][2], R[i][3], FIRST);
        mma4(acc[2 * i + 1], S, s[i][0], s[i][1], FIRST);
    }
    ld_frag(T0, pq - 64); ld_swap(T1, pq + 448);
    add_frag(S, T2, T3);
#pragma unroll
    for (int i = 0; i < 7; i++) {
        if (!FIRST || i) mma4(acc[2 * i + 2], T2, R[i][0], R[i][1]);
        mma4(B[i + 1], T3, R[i][2], R[i][3]);
        mma4(acc[2 * i + 3], S, s[i][0], s[i][1]);
        if (i < NPRE) ldsm4(R[i], va + 16 + i * 256);
    }
}
template <class Wait, class After>
__device__ __forceinline__ void dense_phase(float (&acc)[16][4], uint32_t priv, int lane, Wait wait_for_tokens, After after_loop) {
    const int m = lane >> 3, r = lane & 7;
    const uint32_t pb = priv + T_DENSE + 4 * (15 + (lane >> 2) - 2 * (lane & 3));
    const uint32_t v8 = priv + 128 * (m >> 1) + 16 * r;
    float B[8][4];
    uint32_t T0[4], T1[4], R[8][4];
    uint32_t pq = pb + 512, va = v8 + PLANE * ((m ^ (m >> 1)) & 1);
    ld_frag(T0, pq); ld_swap(T1, pq + 512);
    wait_for_tokens();
#pragma unroll
    for (int i = 0; i < NPRE; i++) ldsm4(R[i], va + i * 256);
    dense_step<true>(acc, B, T0, T1, R, pq, va);
#pragma unroll 1
    do {
        pq -= 64; va += 16;
        dense_step<false>(acc, B, T0, T1, R, pq, va);
    } while (pq != pb + 64);
    after_loop();
    KSTAMP(14, as_h2(0u));
    const uint32_t pp = pb + T_PATCH - T_DENSE - 24;
    uint32_t N0[4], N1[4];
    ld_swap(T1, pb); ld_frag(N0, pp); ld_swap(N1, pp);
#pragma unroll
    for (int i = NPRE; i < 8; i++) ldsm4(R[i], va + 16 + i * 256);
#pragma unroll
    for (int i = 0; i < 8; i++)
#pragma unroll
        for (int j = 0; j < 4; j++) {
            acc[2 * i + 1][j] = (acc[2 * i + 1][j] - acc[2 * i][j]) - B[i][j];
            if (i) acc[2 * i][j] += B[i - 1][j];
        }
#pragma unroll
    for (int i = 0; i < 8; i++) {
        mma4(acc[2 * i], T0, R[i][0], R[i][1]);
        mma4(acc[2 * i + 1], T1, R[i][2], R[i][3]);
        if (i >= 4) {
            mma4(acc[2 * i], N0, R[i - 4][0], R[i - 4][1]);
            mma4(acc[2 * i + 1], N1, R[i - 4][2], R[i - 4][3]);
        }
    }
    const uint32_t b = v8 + PLANE + 112;
    const uint32_t bz = (m & 1) ? priv : b, bm = (m & 1) ? b : b + 512;
    const uint32_t M[4] = {lds32(pb + 4 * 520), lds32(pb + 4 * 528), lds32v(pp + 32), lds32(pp + 64)};
#pragma unroll
    for (int i = 0; i < 6; i++) {
        uint32_t V[4];
        ldsm4(V, i < 2 ? bz + ((m & 1) ? 0 : i * 256) : bm + (i - 2) * 256);
        mma4(acc[2 * i + 4], M, V[0], V[1]);
        mma4(acc[2 * i + 5], M, V[2], V[3]);
    }
}

__device__ __forceinline__ uint32_t ones2(int c, int lo, int n) {
    return (((uint32_t)(c - lo) < (uint32_t)n) ? 0x3f80u : 0u) | (((uint32_t)(c + 1 - lo) < (uint32_t)n) ? 0x3f800000u : 0u);
}
template <int L1, int N1, int L2, int N2, int D>
__device__ __forceinline__ void box_ones(uint32_t dst, int d) { sts128(dst, ones2(d, L1, N1), ones2(d, L2, N2), ones2(d + D, L1, N1), ones2(d + D, L2, N2)); }
__device__ __forceinline__ uint32_t tok_at(int T) { return PLANE * ((T >> 3) & 1) + 16 * ((T >> 4) + 8) + 2 * (T & 7); }
__device__ __forceinline__ float left_col(float cur, float prev, int lane) {
    return __shfl_sync(0xffffffffu, (lane & 3) == 3 ? prev : cur, lane + 3, 4);
}
struct Tails {
    uint4 q4, q8, B4[5], ad;
    uint2 B8[8];
    uint32_t W[2][4], A[2][2][4];
    float p1, p3, p8;
    static __host__ __device__ constexpr bool is8(int k) { return k >= 4 && (k & 1); }
    static __host__ __device__ constexpr int grp(int k) { return k < 4 ? k : (k - 4) / 2 + (is8(k) ? 0 : 4); }
    __device__ __forceinline__ void load(int k, uint32_t priv) {
        uint32_t* w = W[k & 1];
        const uint32_t o = priv + 128 * grp(k);
        if (is8(k)) {
            const uint2 vy = lds64(o + ad.w), vx = lds64(o + ad.z);
            w[0] = vy.x; w[1] = vy.y; w[2] = vx.x; w[3] = vx.y;
        } else { w[0] = lds32(o + ad.y); w[1] = lds32(o + ad.x + 16); w[2] = lds32(o + ad.x); w[3] = lds32v(o + ad.y); }
    }
    __device__ __forceinline__ void box(int k, int lane) {
        const uint32_t* w = W[k & 1];
        const uint4 q = is8(k) ? q8 : q4;
        uint32_t (&a)[2][4] = A[k & 1];
        float X[4], Y[4];
        mma_bf16_z(Y, q.x, q.y, q.z, q.w, w[0], w[1]);
        mma_bf16_z(X, q.x, q.y, q.z, q.w, w[2], w[3]);
        a[0][0] = pack_bf16(X[0], X[1]); a[0][1] = pack_bf16(Y[0], Y[1]);
        if (is8(k)) {
            a[0][2] = pack_bf16(left_col(Y[3], p8, lane), Y[2]); a[0][3] = pack_bf16(X[2], X[3]);
            p8 = Y[3];
        } else {
            a[0][2] = pack_bf16(X[2], X[3]); a[0][3] = pack_bf16(Y[2], Y[3]);
            a[1][0] = pack_bf16(left_col(Y[1], p1, lane), Y[0]); a[1][1] = pack_bf16v(X[0], X[1]);
            a[1][2] = pack_bf16(left_col(Y[3], p3, lane), Y[2]); a[1][3] = pack_bf16v(X[2], X[3]);
            p1 = Y[1]; p3 = Y[3];
        }
    }
    __device__ __forceinline__ void taps(int k, float (&acc)[16][4]) {
        const int G = grp(k);
        if (is8(k)) {
#pragma unroll
            for (int b = 0; b < 8; b++) if (G + 8 + b < 16) mma4(acc[G + 8 + b], A[k & 1][0], B8[b].x, B8[b].y);
        } else {
#pragma unroll
            for (int b = 0; b < 5; b++) if (G + 4 + b < 16) mma4(acc[G + 4 + b], A[k & 1][0], B4[b].x, B4[b].y);
#pragma unroll
            for (int b = 0; b < 5; b++) if (G + 4 + b < 16) mma4(acc[G + 4 + b], A[k & 1][1], B4[b].z, B4[b].w);
        }
    }
    __device__ __forceinline__ void start(uint32_t lc, uint32_t priv, uint32_t tap, int lane) {
        ad = lds128(lc + 1024); q4 = lds128(lc); q8 = lds128(lc + 512);
        p1 = p3 = p8 = 0.f;
        load(0, priv); load(1, priv);
#pragma unroll
        for (int i = 0; i < 5; i++) B4[i] = lds128(priv + T_S4 + 128 * i + 2 * tap);
        box(0, lane);
    }
    template <int K0, int K1>
    __device__ __forceinline__ void run(float (&acc)[16][4], uint32_t priv, uint32_t tap, int lane) {
#pragma unroll
        for (int k = K0; k < K1; k++) {
            if (k + 2 < 20) load(k + 2, priv);
            if (k == 4) {
#pragma unroll
                for (int i = 0; i < 8; i++) B8[i] = lds64(priv + T_S8 + 64 * i + tap);
            }
            if (k + 1 < 20) box(k + 1, lane);
            taps(k, acc);
        }
    }
};
__device__ __forceinline__ void lane_consts(uint32_t dst, int unit, int lane) {
    const int g = lane >> 2, t = lane & 3, m = lane >> 3, r = lane & 7;
    if (unit == 0) box_ones<0, 5, 5, 3, 8>(dst, 2 * t - g);
    else if (unit == 1) box_ones<1, 7, 0, 9, 2>(dst, 4 * t - g);
    else if (unit == 2) sts128(dst, tok_at(16 * g - 10 + 2 * t), tok_at(16 * g - 2 + 2 * t), tok_at(16 * g - 12 + 4 * t), tok_at(16 * g - 4 + 4 * t));
    else {
        const uint32_t low = 64 * (t >> 1) + 32 * (g & 1) + 16 * (t & 1), hi = (lane & 24) + (lane & 16);
        sts128(dst, 128 * hi + low, 512 * (4 * (r & 2) + 2 * m + (r & 1)) + 16 * ((r >> 2) ^ (2 * (r & 3))), 32 * hi + low, 8 * (6 + g - 2 * t));
    }
}

__device__ __forceinline__ uint32_t mean_std(float mu, float var) { return pack_bf16(mu, sqrtaf(bf_round(bf_round(var) + 1e-5f))); }
__device__ __noinline__ uint2 ln_centred(uint32_t sb, float mu) {
    const int lane = threadIdx.x & 31;
    uint32_t ms = 0;
    float res = 0.f, ri = 0.f;
#pragma unroll 1
    for (int mode = 0; mode < 2; mode++) {
#pragma unroll 1
        for (int rr = 0; rr < 16; rr++) {
            const float c0 = __shfl_sync(0xffffffffu, mu, rr), rj = __shfl_sync(0xffffffffu, ri, rr);
            float c = 0.f;
#pragma unroll 1
            for (int k = 0; k < 16; k++) {
                const uint32_t q = lds32(sb + OFF_ROWS + k * 2048 + rr * 128 + ((lane * 4) ^ ((rr & 7) << 4))), wq = lds32(sb + OFF_GP + k * 128 + lane * 4);
                const float d0 = bf_lo(q) - c0, d1 = bf_hi(q) - c0;
                if (mode) c = fmaf(bf_round(bf_round(d0) * rj), bf_lo(wq), fmaf(bf_round(bf_round(d1) * rj), bf_hi(wq), c));
                else c = fmaf(d0, d0, fmaf(d1, d1, c));
            }
#pragma unroll 1
            for (int o = 16; o; o >>= 1) c += __shfl_xor_sync(0xffffffffu, c, o);
            if ((lane & 15) == rr) res = c;
        }
        if (mode == 0) { ms = mean_std(mu, res * (1.f / DM)); mu = bf_lo(ms); ri = rcpf(bf_hi(ms)); }
    }
    named_sync(1, 128);
    return make_uint2(ms, __float_as_uint(res));
}

__device__ __forceinline__ void router_cta(uint32_t* scr, uint32_t sb, uint32_t zero, int tid, int warp) {
    const int lane = tid & 31;
    const uint32_t cand = sb + 128;
    const uint32_t epoch = ld_relaxed_32(scr + S_EPOCH);
    if (tid < 128) st_relaxed_32(scr + S_SEL + tid, 0u);
    if (tid == 0) sts32(sb + 64, cand);
    sts128(cand + 16 * tid, 0, 0, 0, 0);
    asm volatile("fence.acq_rel.gpu;" ::: "memory");
    const uint32_t tag = (epoch + 1u) | 0x8000u;
    STAMP(0); GSTAMP(1);
    uint32_t* const psel = scr + S_SEL + 32 * (lane & 3);
    const uint32_t cnt = sb + 64 + (tid & zero);
    uint32_t it = 0;
    uint4 q;
#pragma unroll 1
    do {
        q = ld_relaxed_128(scr + S_KEY + 4 * tid);
        if (++it > SPIN_LIMIT) __trap();
    } while (!__all_sync(0xffffffffu, (((q.x ^ tag) | (q.y ^ tag) | (q.z ^ tag) | (q.w ^ tag)) & 0xffffu) == 0));
    STAMP(2);
    uint32_t key[4] = {q.x, q.y, q.z, q.w};
#pragma unroll
    for (int j = 0; j < 4; j++) key[j] = ((key[j] ^ ((uint32_t)((int)key[j] >> 31) | 0x80000000u)) & 0xffff0000u) | (0xffffu - (uint32_t)(4 * tid + j));
    const uint32_t gm = __reduce_max_sync(0xffffffffu, max(max(key[0], key[1]), max(key[2], key[3])));
    sts32(sb + 4 * warp, gm);
    __syncthreads();
    const uint2 pr = lds64(sb + 8 * (lane & 7));
    const uint32_t tau = __reduce_min_sync(0xffffffffu, max(pr.x, pr.y));
    asm volatile("{\n\t.reg .pred p<4>;\n\t.reg .u32 a<4>;\n\t"
                 "setp.ge.u32 p0, %0, %4;\n\tsetp.ge.u32 p1, %1, %4;\n\tsetp.ge.u32 p2, %2, %4;\n\tsetp.ge.u32 p3, %3, %4;\n\t"
                 "@p0 atom.shared.add.u32 a0, [%5], 4;\n\t@p1 atom.shared.add.u32 a1, [%5], 4;\n\t"
                 "@p2 atom.shared.add.u32 a2, [%5], 4;\n\t@p3 atom.shared.add.u32 a3, [%5], 4;\n\t"
                 "@p0 st.shared.u32 [a0], %0;\n\t@p1 st.shared.u32 [a1], %1;\n\t@p2 st.shared.u32 [a2], %2;\n\t@p3 st.shared.u32 [a3], %3;\n\t}"
                 ::"r"(key[0]), "r"(key[1]), "r"(key[2]), "r"(key[3]), "r"(tau), "r"(cnt) : "memory");
    __syncthreads();
    STAMP(6);
    const uint32_t c0 = lds32v(cand + 4 * lane);
    uint2 k = lds64(cand + 8 * warp);
    const uint32_t end = __shfl_sync(0xffffffffu, lds32v(sb + 64), 0);
    uint32_t i = cand + 8 * warp;
#pragma unroll 1
    do {
        uint32_t r0 = __popc(__ballot_sync(0xffffffffu, c0 > k.x)), r1 = __popc(__ballot_sync(0xffffffffu, c0 > k.y));
#pragma unroll 1
        for (uint32_t j = cand + 128; j < end; j += 128) {
            const uint32_t c = lds32(j + 4 * lane);
            r0 += __popc(__ballot_sync(0xffffffffu, c > k.x)); r1 += __popc(__ballot_sync(0xffffffffu, c > k.y));
        }
        const uint32_t rk = (lane & 4) ? r1 : r0;
        if (rk < 8 && lane < 8) st_relaxed_64(psel + 2 * rk, (lane & 4) ? k.y : k.x, tag);
        i += 128;
        k = lds64(i);
    } while (i < end);
    STAMP(4); GSTAMP(5);
    if (tid == 0) st_relaxed_32(scr + S_EPOCH, epoch + 1u);
}

__global__ void __cluster_dims__(2, 1, 1) __launch_bounds__(NTHR, 1)
fused_kernel(const __grid_constant__ Ptrs p, const __grid_constant__ Maps maps) {
    extern __shared__ __align__(1024) unsigned char smem[];
    const uint32_t sb = s_u32(smem);
    const int tid = threadIdx.x, lane = tid & 31;
    const int warp = __shfl_sync(0xffffffffu, tid >> 5, 0);
    const int b = blockIdx.x, h = b & 1, cl = b >> 1;
    const uint32_t bar0 = sb + OFF_BAR;
    const int m = lane >> 3, r = lane & 7;
    if (b >= NCTA) {
        if (b == NCTA) router_cta(p.scr, sb, p.zero, tid, warp);
        return;
    }
    if (warp < 8) {
        const int w = warp, dch = 8 * b + w;
        STAMP(0);
        const int po = dch * NMODE + 4 * lane;
        const uint2 la = ldg64(p.logA + po), aim = ldg64(p.Aim + po), cre = ldg64(p.Cre + po), cim = ldg64(p.Cim + po);
        const uint32_t ldt16 = ldg16(p.ldt + dch), dsk16 = ldg16(p.dsk + dch);
        cluster_arrive();
        asm volatile("setmaxnreg.inc.sync.aligned.u32 %0;" ::"n"(CONV_REGS));
        const uint32_t priv = sb + OFF_PRIV + w * PRIV;
        const int g = lane >> 2, t = lane & 3;
        float kacc[5][4], kscale;
        {
            const uint32_t m2 = as_u(__hmax2(__hmax2(__habs2(as_b2(cre.x)), __habs2(as_b2(cre.y))), __hmax2(__habs2(as_b2(cim.x)), __habs2(as_b2(cim.y)))));
            const uint32_t eb = min(max(__reduce_max_sync(0xffffffffu, max(m2 << 16, m2)) >> 23, 1u), 252u);
            const float dt = bf_round(ex2f(bf_lo(ldt16) * L2E));
            STAMP(1);
            kgen_mma(kacc, priv, lane, la, aim, cre, cim, dt, (253u - eb) * 0x00800080u);
            STAMP(2);
            cluster_wait();
            __syncwarp();
            if (elect_one()) mbar_arrive(bar0 + 8 * B_KG);
            float s0[4];
            mma_bf16_z(s0, ONES, ONES, ONES, ONES, cre.x, cre.y);
            float k0 = s0[0] + s0[1];
            k0 += __shfl_xor_sync(0xffffffffu, k0, 1);
            k0 += __shfl_xor_sync(0xffffffffu, k0, 2);
            kscale = (dt + dt) * __uint_as_float((eb + 1u) << 23);
            kgen_tables(kacc, priv, lane, kscale, fmaf(k0, dt + dt, bf_lo(dsk16) + 1.f));
        }
        STAMP(3);
        kgen_tables2(kacc, priv, lane, kscale);
        STAMP(4);
        float acc[16][4];
        dense_phase(acc, priv, lane, [&]() {
            mbar_wait(bar0 + 8 * B_VT, 0);
            STAMP(6);
        }, [&]() { mbar_wait(bar0 + 8 * B_PV, 0); });
        STAMP(7);
        const uint32_t sd = sb + OFF_X + 512 * (8 * h + w) + 16 * (lane ^ (2 * (w & 1) + 4 * h));
        const uint32_t sd0 = mapa(sd + 8192, 0), sd1 = mapa(sd, 1);
        auto send = [&](auto PT) {
            constexpr int pt = decltype(PT)::value;
#pragma unroll
            for (int i = 0; i < 2; i++) {
                const float* c0 = acc[4 * pt + 2 * i];
                const float* c1 = acc[4 * pt + 2 * i + 1];
                asm volatile("st.async.weak.shared::cluster.mbarrier::complete_tx::bytes.v4.b32 [%0 + %6], {%1,%2,%3,%4}, [%5];"
                             ::"r"(i ? sd1 : sd0), "r"(pack_bf16(c0[0], c0[1])), "r"(pack_bf16(c0[2], c0[3])), "r"(pack_bf16(c1[0], c1[1])),
                               "r"(pack_bf16(c1[2], c1[3])), "r"(mapa(bar0 + 8 * (B_RECV + pt), i)), "n"(16384 * pt) : "memory");
            }
        };
        const uint4 lc = lds128(sb + OFF_LC + 1536 + 16 * lane);
        const uint32_t stg = (priv + T_DENSE + 63) & ~127u, so = stg + lc.z;
        const uint32_t xa = sb + OFF_X + 16384 * (w >> 2) + 8192 * h + 256 * (w & 3) + lc.x;
        const uint32_t sa = sb + OFF_X + 16384 * (w >> 2) + 8192 * (h ^ 1) + 128 * (w & 3) + lc.y;
        auto finish = [&](int ph) {
            const int box = 4 * ph + 2 * (w >> 2) + h;
            uint4 x[4];
            uint32_t s[4][4];
#pragma unroll
            for (int i = 0; i < 4; i++) x[i] = lds128((xa ^ (8 * (i & 2))) + 32768 * ph + 2048 * (i & 1) + 64 * (i & 2));
            mbar_wait(bar0 + 8 * (B_RECV + 2 * ph + (w >> 2)), 0);
            const uint32_t routed = __shfl_sync(0xffffffffu, lds32(sb + OFF_MISC + 4), 0);
#pragma unroll
            for (int i = 0; i < 4; i++) ldsm4t(s[i], (sa ^ (32 * i)) + 32768 * ph);
#pragma unroll
            for (int i = 0; i < 4; i++) { s[i][0] = badd2(x[i].x, s[i][0]); s[i][1] = badd2(x[i].y, s[i][1]); s[i][2] = badd2(x[i].z, s[i][2]); s[i][3] = badd2(x[i].w, s[i][3]); }
            if ((routed >> (4 * box + (w & 3))) & 1) {
                const uint32_t tk = 256 * box + 128 * (g >> 2) + 32 * (t >> 1) + 16 * (g & 1) + 4 * (g & 2) + 2 * (w & 3);
                const uint32_t mk[2] = {lds32(sb + OFF_MISC + 32 + 4 * (tk >> 5)) >> (tk & 31), lds32(sb + OFF_MISC + 40 + 4 * (tk >> 5)) >> (tk & 31)};
                __nv_bfloat16* o = p.out + (size_t)tk * DM + 16 * cl + 8 * (t & 1);
#pragma unroll
                for (int i = 0; i < 4; i++)
                    asm volatile("{\n\t.reg .pred p;\n\tsetp.eq.u32 p, %6, 0;\n\t@!p st.shared.v4.u32 [%1], {%2,%3,%4,%5};\n\t@p st.global.v4.u32 [%0], {%2,%3,%4,%5};\n\t}"
                                 ::"l"(o + (64 * (i & 1) + (i >> 1)) * DM), "r"((xa ^ (8 * (i & 2))) + 32768 * ph + 2048 * (i & 1) + 64 * (i & 2)),
                                   "r"(s[i][0]), "r"(s[i][1]), "r"(s[i][2]), "r"(s[i][3]), "r"(mk[i & 1] & (1u << (i >> 1))) : "memory");
            } else {
#pragma unroll
                for (int i = 0; i < 4; i++) sts128(so - 2048 * ph + 512 * (i & 1) + 64 * (i & 2), s[i][0], s[i][1], s[i][2], s[i][3]);
                fence_async();
                __syncwarp();
                if (elect_one()) {
                    asm volatile("cp.async.bulk.tensor.5d.global.shared::cta.bulk_group [%0, {%2, %5, %3, %5, %4}], [%1];"
                                 ::"l"(&maps.out), "r"(stg - 2048 * ph), "r"(16 * cl), "r"(2 * (w & 3)), "r"(4 * box), "r"(0) : "memory");
                }
            }
        };
        Tails tl;
        tl.start(sb + OFF_LC + 16 * lane, priv, lc.w, lane);
        send(IC<0>());
        tl.run<0, 4>(acc, priv, lc.w, lane);
        send(IC<1>());
        STAMP(8);
        if (w < 4) finish(0);
        tl.run<4, 12>(acc, priv, lc.w, lane);
        send(IC<2>());
        STAMP(9);
        if (w >= 4) finish(0);
        tl.run<12, 20>(acc, priv, lc.w, lane);
        STAMP(11);
        send(IC<3>());
        finish(1);
        STAMP(12);
        __syncwarp();
        if (elect_one()) mbar_arrive(bar0 + 8 * B_ST);
        asm volatile("cp.async.bulk.commit_group;" ::: "memory");
        asm volatile("cp.async.bulk.wait_group.read 0;" ::: "memory");
        STAMP(13); GSTAMP(15);
    } else if (warp < 12) {
        const int a = warp - 8, at = 32 * a + lane, g = lane >> 2, t = lane & 3;
        STAMP(0);
        if (elect_one()) {
            const uint32_t cnt = a == 3 ? 0x18411122u : a == 2 ? 0x44444444u : 0x11111111u, tx = a == 0 ? 0x44444444u : a == 3 ? 0x00084444u : 0u;
#pragma unroll 1
            for (int i = 0; i < 8; i++) {
                mbar_init(bar0 + 64 * a + 8 * i, (cnt >> (4 * i)) & 15);
                const uint32_t n = (tx >> (4 * i)) & 15;
                if (n) mbar_expect_tx(bar0 + 64 * a + 8 * i, n << 11);
            }
            if (a < 3) mbar_init(bar0 + 8 * (B_KG + a), a ? 4 : 8);
            asm volatile("fence.mbarrier_init.release.cluster;" ::: "memory");
            fence_async();
        }
        __syncwarp();
        cluster_arrive();
        asm volatile("setmaxnreg.inc.sync.aligned.u32 %0;" ::"n"(FFN_REGS));
        const uint32_t epoch = ld_relaxed_32(p.scr + S_EPOCH);
        uint32_t* const pst = p.scr + S_STAT + 2048 * a + 16 * b + 2 * r + m;
        uint32_t* const pky = p.scr + S_KEY + 16 * b + at;
        if (at < 16) st_relaxed_32(pky, 0u);
        uint32_t* const py = p.scr + S_Y + 1024 * ((cl & ~3) + a) + 128 * (b & 7) + 32 * t + 4 * g;
        const uint32_t gp = sb + OFF_GP;
        sts32(gp + 2048 + 4 * lane, ONES);
        lane_consts(sb + OFF_LC + 16 * at, a, lane);
        cluster_wait();
        STAMP(1);
        if (lane < 16) st_relaxed_32(pst, epoch << 31);
        mbar_wait(bar0 + 8 * B_WR, 0);
        float wsum;
        {
            const uint4 q = lds128(gp + 16 * at);
            wsum = ((bf_lo(q.x) + bf_hi(q.x)) + (bf_lo(q.y) + bf_hi(q.y))) + ((bf_lo(q.z) + bf_hi(q.z)) + (bf_lo(q.w) + bf_hi(q.w)));
#pragma unroll
            for (int o = 16; o; o >>= 1) wsum += __shfl_xor_sync(0xffffffffu, wsum, o);
            sts32(gp + 2176 + 4 * a, __float_as_uint(wsum));
        }
        const uint32_t hsel = (epoch & 1) * (GU_CTAS * 128), want = (epoch & 1) ? 0u : 0x80008000u;
        const uint32_t tbit = ~epoch << 31, ktag = ((epoch + 1u) | 0x8000u) & 0xffffu;
        if (a == 0) sts64(sb + OFF_MISC + 32 + 8 * lane, 0u, 0u);
        if (b < GU_CTAS) st_relaxed_32(p.scr + S_H + (GU_CTAS * 128 - hsel) + b * 128 + at, 0u);
        {
            uint32_t ra[4], rs;
#pragma unroll
            for (int i = 0; i < 4; i++) {
                ra[i] = (m & 1) ? (r == 1 ? gp + 128 * a + 32 * i + 16 * (m >> 1) : gp + 2048) : sb + OFF_ROWS + 2048 * a + 128 * r + (((2 * i + (m >> 1)) ^ r) << 4);
            }
            rs = (m & 1) ? (r == 1 ? 512 : 0) : 8192;
            const uint32_t r8 = (m & 1) ? 0 : 1024;
            float cs[4][4] = {};
#pragma unroll 1
            for (int k = 0; k < 4; k++) {
                uint32_t x[4][4], y[4][4];
                mbar_wait(bar0 + 8 * (B_ROW + k), 0);
#pragma unroll
                for (int i = 0; i < 4; i++) {
                    ldsm4(x[i], ra[i]); ldsm4(y[i], ra[i] + r8);
                    ra[i] += rs;
                }
#pragma unroll
                for (int i = 0; i < 4; i++) {
                    mma4(cs[2 * (i & 1)], x[i], x[i][0], x[i][2]);
                    mma4(cs[2 * (i & 1) + 1], y[i], y[i][0], y[i][2]);
                }
            }
            const uint32_t pa = gp + 2304 + 4 * a;
#pragma unroll
            for (int i = 0; i < 8; i++) cs[i >> 2][i & 3] += cs[2 + (i >> 2)][i & 3];
            if (g < 2) {
#pragma unroll
                for (int i = 0; i < 4; i++) sts32(pa + 256 * g + 32 * t + 128 * (i >> 1) + 16 * (i & 1), __float_as_uint(cs[i >> 1][2 + (i & 1)]));
            }
            if (t == (g >> 1)) {
                sts32(pa + 512 + 16 * g, __float_as_uint((g & 1) ? cs[0][1] : cs[0][0]));
                sts32(pa + 640 + 16 * g, __float_as_uint((g & 1) ? cs[1][1] : cs[1][0]));
            }
            named_sync(1, 128);
            auto sum4 = [](uint4 q) { return (__uint_as_float(q.x) + __uint_as_float(q.y)) + (__uint_as_float(q.z) + __uint_as_float(q.w)); };
            const uint32_t o = gp + 2304 + 16 * (lane & 15);
            const float mu = sum4(lds128(o)) * (1.f / DM), e2 = sum4(lds128(o + 512)) * (1.f / DM), var = fmaf(-mu, mu, e2);
            const float sw = sum4(lds128(o + 256));
            wsum = sum4(lds128(gp + 2176));
            uint32_t ms = mean_std(mu, var);
            float sc = (sw - bf_round(mu) * wsum) * rcpf(bf_hi(ms));
            if (__any_sync(0xffffffffu, !(e2 <= 65.f * var))) {
                const uint2 c = ln_centred(sb, mu);
                ms = c.x; sc = __uint_as_float(c.y);
            }
            if (lane < 16 && a < 2) st_relaxed_32(pst, ms | tbit);
            if (at < 16) st_relaxed_32(pky, pack_bf16(0.f, sc) | ktag);
            if (lane < 8) mbar_arrive(bar0 + 8 * (B_EMPTY + lane));
        }
        STAMP(3); GSTAMP(14);
        {
            const uint32_t* sp = p.scr + S_STAT + 2048 * (cl & 1) + 512 * a + 16 * t + 2 * g;
            uint2 sq[8];
            uint32_t s2[8], bad;
            mbar_wait(bar0 + 8 * (B_X + 4 * h + 3), 0);
#pragma unroll 1
            do {
                __nanosleep(0);
#pragma unroll
                for (int i = 0; i < 8; i++) sq[i] = ld_relaxed_64(sp + 64 * i);
                bad = 0;
#pragma unroll
                for (int i = 0; i < 8; i++) { s2[i] = __byte_perm(sq[i].x, sq[i].y, 0x7632) ^ want; bad |= s2[i]; }
            } while (!__all_sync(0xffffffffu, (bad & 0x80008000u) == 0));
            STAMP(13);
            const uint32_t xa = sb + OFF_X + 16384 * a + 32 * lane + ((h ^ (g & 1)) << 4);
            const uint32_t dst = sb + OFF_PRIV + (2 * m + (r & 1)) * PRIV + 128 + 512 * a + 16 * (r >> 1);
#pragma unroll
            for (int bk = 0; bk < 2; bk++) {
                mbar_wait(bar0 + 8 * (B_X + 2 * a + bk), 0);
                uint32_t v[8][4];
#pragma unroll
                for (int i = 0; i < 4; i++) {
                    const uint2 rc = recip2(s2[4 * bk + i]), st = sq[4 * bk + i];
#pragma unroll
                    for (int hf = 0; hf < 2; hf++) {
                        const __nv_bfloat162 mm = __low2bfloat162(as_b2(hf ? st.y : st.x));
                        const __nv_bfloat162 rh = hf ? __high2bfloat162(as_b2(rc.x)) : __low2bfloat162(as_b2(rc.x));
                        const __nv_bfloat162 rl = hf ? __high2bfloat162(as_b2(rc.y)) : __low2bfloat162(as_b2(rc.y));
                        const uint4 q = lds128(xa + 8192 * bk + 2048 * i + 1024 * hf);
                        uint32_t* o = v[2 * i + hf];
                        o[0] = normalize2(q.x, mm, rh, rl); o[1] = normalize2(q.y, mm, rh, rl); o[2] = normalize2(q.z, mm, rh, rl); o[3] = normalize2(q.w, mm, rh, rl);
                    }
                }
                if (bk == 0) mbar_wait(bar0 + 8 * B_KG, 0);
#pragma unroll
                for (int i = 0; i < 8; i++) stsm4t(dst + 256 * bk + 64 * (i >> 1) + PLANE * (i & 1), v[i]);
            }
            __syncwarp();
            if (elect_one()) { mbar_arrive(bar0 + 8 * B_VT); mbar_arrive_peer(mapa(bar0 + 8 * B_PV, h ^ 1)); }
            __syncwarp();
        }
        uint32_t mykey;
        {
            const uint32_t* sl = p.scr + S_SEL + 32 * (cl & 3) + 2 * g;
            uint2 q;
#pragma unroll 1
            do {
                __nanosleep(40);
                q = ld_relaxed_64(sl);
            } while (!__all_sync(0xffffffffu, q.y == ((epoch + 1u) | 0x8000u)));
            mykey = q.x;
        }
        STAMP(4);
        if (a == 0) {
            const uint32_t tok = ~mykey & 0xffffu;
            if (t == 0) asm volatile("red.shared.or.b32 [%0], %1;" ::"r"(sb + OFF_MISC + 32 + 4 * (tok >> 5)), "r"(1u << (tok & 31u)) : "memory");
            sts32(sb + OFF_MISC + 4, __reduce_or_sync(0xffffffffu, 1u << (4 * (tok >> 8) + ((tok >> 1) & 3))));
            __syncwarp();
            if (elect_one()) { mbar_arrive(bar0 + 8 * B_RECV); mbar_arrive(bar0 + 8 * (B_RECV + 1)); }
        }
        if (b < GU_CTAS) {
            const uint32_t tok = 0xffffu - (mykey & 0xffffu);
            {
                const uint32_t tk = __shfl_sync(0xffffffffu, tok, 16 * h + 4 * a);
                if (elect_one())
                    asm volatile("cp.async.bulk.shared::cluster.global.mbarrier::complete_tx::bytes.multicast::cluster [%0], [%1], 2048, [%2], %3;"
                                 ::"r"(sb + OFF_XS + (4 * h + a) * ROW_PITCH), "l"(p.u + (size_t)tk * DM), "r"(bar0 + 8 * B_XS), "h"((uint16_t)3) : "memory");
            }
            uint2 rec;
#pragma unroll 1
            do {
                rec = ld_relaxed_64(p.scr + S_STAT + 2048 * (a & 1) + (tok & ~15u) + 2 * (tok & 7u));
            } while (!__all_sync(0xffffffffu, ((__byte_perm(rec.x, rec.y, 0x7632) ^ want) & 0x80008000u) == 0));
            const uint32_t mst = (tok & 8u) ? rec.y : rec.x;
            const uint32_t m2 = __byte_perm(mst, 0, 0x1010);
            const float rs = rcpf(__uint_as_float(mst & 0x7fff0000u));
            const float r0 = __shfl_sync(0xffffffffu, rs, 8 * t), r1 = __shfl_sync(0xffffffffu, rs, 8 * t + 4);
            float gacc[4][4] = {};
            const int k = r + 8 * (m >> 1);
            uint32_t wa[4];
#pragma unroll
            for (int mt = 0; mt < 4; mt++) wa[mt] = 1024 * a + (((m & 1) * 4096) ^ p.up_first) + k * 64 + ((((k >> 1) & 3) ^ mt) << 4);
            const uint32_t xa = sb + OFF_XS + r * ROW_PITCH + 32 * a + 16 * (m & 1) + 128 * (m >> 1);
#pragma unroll 1
            for (int c = 0; c < 4; c++) {
                uint32_t af[4][4][4], xb[2][4];
                const uint32_t half = sb + OFF_RING + 32768 * (c & 1), fb = bar0 + 8 * B_FULL + 32 * (c & 1);
#pragma unroll
                for (int j = 0; j < 4; j++) {
                    mbar_wait(fb + 8 * j, c >> 1);
                    if (j == 3) STAMP(12);
#pragma unroll
                    for (int mt = 0; mt < 4; mt++) ldsm4t(af[j][mt], wa[mt] + half + j * 8192);
                    __syncwarp();
                    if (elect_one()) mbar_arrive(fb + 8 * (B_EMPTY - B_FULL + j));
                    if (j == 2) {
                        mbar_wait(bar0 + 8 * B_XS, 0);
#pragma unroll
                        for (int i = 0; i < 2; i++) {
                            ldsm4(xb[i], xa + 512 * c + 256 * i);
#pragma unroll
                            for (int e = 0; e < 4; e++) xb[i][e] = as_u(__hsub2(as_b2(xb[i][e]), as_b2(m2)));
                        }
                    }
                    if (j == 3) STAMP(1);
                    if (j >= 2) {
#pragma unroll
                        for (int ks = j == 2 ? 0 : j; ks <= j; ks++) {
#pragma unroll
                            for (int mt = 0; mt < 4; mt++)
                                mma_bf16v(gacc[mt], af[ks][mt], xb[ks >> 1][2 * (ks & 1)], xb[ks >> 1][2 * (ks & 1) + 1]);
                        }
                    }
                }
            }
            STAMP(6);
#pragma unroll
            for (int mt = 0; mt < 4; mt++) sts128f(gp + 2048 * a + mt * 512 + lane * 16, gacc[mt]);
            named_sync(1, 128);
            {
                uint4 q[4];
#pragma unroll
                for (int wq = 0; wq < 4; wq++) q[wq] = lds128(gp + 2048 * wq + 16 * at);
                const uint32_t g2 = pack_bf16(r0 * ((__uint_as_float(q[0].x) + __uint_as_float(q[1].x)) + (__uint_as_float(q[2].x) + __uint_as_float(q[3].x))),
                                              r1 * ((__uint_as_float(q[0].y) + __uint_as_float(q[1].y)) + (__uint_as_float(q[2].y) + __uint_as_float(q[3].y))));
                const uint32_t u2 = pack_bf16(r0 * ((__uint_as_float(q[0].z) + __uint_as_float(q[1].z)) + (__uint_as_float(q[2].z) + __uint_as_float(q[3].z))),
                                              r1 * ((__uint_as_float(q[0].w) + __uint_as_float(q[1].w)) + (__uint_as_float(q[2].w) + __uint_as_float(q[3].w))));
                const uint32_t s2 = pack_bf16(bf_lo(g2) * rcpf(1.f + ex2f(-L2E * bf_lo(g2))), bf_hi(g2) * rcpf(1.f + ex2f(-L2E * bf_hi(g2))));
                uint32_t hw;
                asm volatile("movmatrix.sync.aligned.m8n8.trans.b16 %0, %1;" : "=r"(hw) : "r"(as_u(__hmul2(as_b2(s2), as_b2(u2)))));
                if (hw == 0u) hw = 0x80008000u;
                st_relaxed_32(p.scr + S_H + hsel + b * 128 + at, hw);
            }
            STAMP(7);
        }
        const uint32_t ytag = 1u + (epoch & 1);
        {
            const uint32_t* hp = p.scr + S_H + hsel + (b & 7) * 1792 + 64 * a + lane;
            uint32_t wa[4], af[6][4][4], hb[14];
#pragma unroll
            for (int mt = 0; mt < 4; mt++) wa[mt] = sb + OFF_RING + 2048 * a + 128 * (r + 8 * (m >> 1)) + (((2 * mt + (m & 1)) ^ r) << 4);
            float dacc[4][4] = {};
            auto load_w = [&](int s) {
                mbar_wait(bar0 + 8 * (B_FULL + s), 0);
#pragma unroll
                for (int j = 0; j < 4; j++) ldsm4t(af[s % 6][j], wa[j] + s * 8192);
            };
            auto run = [&](int s) {
#pragma unroll
                for (int j = 0; j < 4; j++) mma_bf16v(dacc[j], af[s % 6][j], hb[2 * s], hb[2 * s + 1]);
            };
            auto look = [&]() {
#pragma unroll
                for (int j = 0; j < 14; j++) hb[j] = ld_relaxed_32(hp + 256 * (j >> 1) + 32 * (j & 1));
            };
            auto missing = [&]() {
                uint32_t mn = hb[0];
#pragma unroll
                for (int j = 1; j < 14; j++) mn = min(mn, hb[j]);
                return __any_sync(0xffffffffu, mn == 0);
            };
            load_w(0);
            st_relaxed_128(py, 0u, 0u, 0u, 0u);
            bool again = true;
            if (b >= GU_CTAS) { look(); again = missing(); }
#pragma unroll
            for (int s = 1; s < 5; s++) load_w(s);
            if (again) look();
            load_w(5);
#pragma unroll 1
            while (missing()) { __nanosleep(0); look(); }
            STAMP(2);
#pragma unroll
            for (int s = 0; s < 6; s++) run(s);
            load_w(6);
            run(6);
            STAMP(8);
#pragma unroll
            for (int mt = 0; mt < 4; mt++) sts128f(sb + OFF_XS + 2048 * a + mt * 512 + lane * 16, dacc[mt]);
            named_sync(1, 128);
            uint4 q[4];
#pragma unroll
            for (int wq = 0; wq < 4; wq++) q[wq] = lds128(sb + OFF_XS + 2048 * wq + 16 * at);
            auto tagged = [&](uint32_t x0, uint32_t x1, uint32_t x2, uint32_t x3) {
                return (__float_as_uint((__uint_as_float(x0) + __uint_as_float(x1)) + (__uint_as_float(x2) + __uint_as_float(x3))) & ~3u) | ytag;
            };
            st_relaxed_128(py, tagged(q[0].x, q[1].x, q[2].x, q[3].x), tagged(q[0].y, q[1].y, q[2].y, q[3].y),
                           tagged(q[0].z, q[1].z, q[2].z, q[3].z), tagged(q[0].w, q[1].w, q[2].w, q[3].w));
        }
        STAMP(9);
        {
            const uint32_t key = __shfl_sync(0xffffffffu, mykey, 8 * a + 4 * (m >> 1));
            const uint32_t tok = 0xffffu - (key & 0xffffu);
            const float sg = bf_round(rcpf(1.f + ex2f(-L2E * bf_lo(unorder_key(key >> 16)))));
            const uint32_t xo = sb + OFF_X + 32 * (tok & ~63u) + 128 * (tok & 15u) + 2 * (tok & 48u) + ((2 * (lane & 15)) ^ ((tok & 1u) << 4));
            const bool mine = ((tok >> 8) & 1) == h;
            if (elect_one()) mbar_arrive(bar0 + 8 * B_DONE);
            if (mine) {
                const uint32_t* yp = p.scr + S_Y + 1024 * cl + 32 * a + 4 * r + 2 * (m & 1) + (m >> 1);
                uint32_t pp[8], bad, it = 0, o;
#pragma unroll 1
                do {
                    if (++it > SPIN_LIMIT) __trap();
                    bad = 0;
#pragma unroll
                    for (int q = 0; q < 8; q++) pp[q] = ld_relaxed_32(yp + 128 * q);
#pragma unroll
                    for (int q = 0; q < 8; q++) bad |= pp[q] ^ ytag;
                } while (bad & 3u);
                const float y = ((__uint_as_float(pp[0]) + __uint_as_float(pp[1])) + (__uint_as_float(pp[2]) + __uint_as_float(pp[3]))) +
                                ((__uint_as_float(pp[4]) + __uint_as_float(pp[5])) + (__uint_as_float(pp[6]) + __uint_as_float(pp[7])));
                const uint32_t upd = pack_bf16(bf_round(y) * sg, 0.f);
                STAMP(11);
                mbar_wait(bar0 + 8 * B_ST, 0);
                asm volatile("ld.shared.u16 %0, [%1];" : "=r"(o) : "r"(xo));
                asm volatile("st.global.u16 [%0], %1;" ::"l"(p.out + (size_t)tok * DM + 16 * cl + (lane & 15)), "r"(badd2(o, upd)) : "memory");
            }
        }
        STAMP(10); GSTAMP(15);
    } else {
        asm volatile("setmaxnreg.dec.sync.aligned.u32 %0;" ::"n"(PROD_REGS));
        const int q = warp - 12;
        sts32(sb + OFF_MISC + 16 + 4 * q, clk());
        const uint32_t t0 = __shfl_sync(0xffffffffu, lds32v(sb + OFF_MISC + 16 + 4 * q), 0);
        STAMP(0);
        if (q == 1) GSTAMP(14);
        const bool one = elect_one();
        const uint32_t rbar = bar0 + 8 * (B_ROW + q);
        if (one) {
            asm volatile("prefetch.tensormap [%0];" ::"l"(&maps.rows) : "memory");
            mbar_init(rbar, 1);
            if (q == 3) mbar_init(bar0 + 8 * B_WR, 1);
            fence_async();
            mbar_expect_tx(rbar, 8192);
            if (q == 3) {
                mbar_expect_tx(bar0 + 8 * B_WR, 2048);
                bulk_g2s(sb + OFF_GP, p.wr, 2048, bar0 + 8 * B_WR);
            }
        }
        __syncwarp();
        cluster_arrive();
        wait_until(t0 + ROW_DELAY + q * ROW_PERIOD);
        if (one) {
            tma_load_3d(sb + OFF_ROWS + 8192 * q, &maps.rows, 16 * b, 4 * q, rbar);
            asm volatile("prefetch.tensormap [%0];" ::"l"(&maps.u + q) : "memory");
        }
        __syncwarp();
        cluster_wait();
        STAMP(1);
        wait_until(t0 + X_DELAY + q * 60);
        if (one) tma_load_4d_both(sb + OFF_X + 8192 * (4 * h + q), &maps.u, 16 * cl, 4 * (4 * h + q), bar0 + 8 * (B_X + 4 * h + q));
        STAMP(2);
        const char* src = (const char*)((b >> 6) ? p.wu : p.wg) + (64 * q + (b & 63)) * 7168 + 128 * lane;
        const uint32_t phase = t0 + PF_START + (b * PF_PERIOD >> 7) + q * PF_PERIOD;
        auto fill = [&](int j, uint32_t due, const CUtensorMap* map, int c0, int c3) {
            const uint32_t bar = bar0 + 8 * (B_FULL + q + 4 * (j & 1));
            wait_until(due);
            mbar_wait_bounded(bar + 8 * (B_EMPTY - B_FULL), (j >> 1) & 1);
            if (one) {
                mbar_expect_tx(bar, 8192);
                tma_load_4d(sb + OFF_RING + (q + 4 * (j & 1)) * 8192, map, c0, c3, bar);
            }
            STAMP(3 + (j >> 1));
        };
#pragma unroll 1
        for (int j = 0; j < 4; j++) {
            wait_until(phase + 4 * j * PF_PERIOD);
            asm volatile("prefetch.global.L2 [%0];" ::"l"(src) : "memory");
            if (lane < 24) asm volatile("prefetch.global.L2 [%0];" ::"l"(src + 4096) : "memory");
            src += 256 * 7168;
            STAMP(6);
            if (b < GU_CTAS) fill(j, t0 + LD_START + (b * LD_SPREAD >> 7) + (q + 4 * j) * LD_PERIOD, &maps.wgu, 32 * b, q + 4 * j);
        }
#pragma unroll 1
        for (int j = 4; j < (q < 3 ? 6 : 5); j++)
            fill(j, phase + 4 * j * PF_PERIOD + (q + 4 * j - 16) * WD_EXTRA, &maps.wd, 64 * (b >> 3), 7 * (b & 7) + q + 4 * j - 16);
        if (q >= 2) mbar_wait_bounded(bar0 + 8 * (q == 2 ? B_DONE : B_RECV + 3), 0);
    }
}

typedef CUresult (*EncodeFn)(CUtensorMap*, CUtensorMapDataType, cuuint32_t, void*, const cuuint64_t*, const cuuint64_t*,
                             const cuuint32_t*, const cuuint32_t*, CUtensorMapInterleave, CUtensorMapSwizzle,
                             CUtensorMapL2promotion, CUtensorMapFloatOOBfill);

void make_map(EncodeFn enc, CUtensorMap* m, int rank, const void* ptr, const cuuint64_t (&dims)[5], const cuuint64_t (&str)[4],
              const cuuint32_t (&box)[5], CUtensorMapSwizzle sw, CUtensorMapL2promotion pr) {
    const cuuint32_t es[5] = {1, 1, 1, 1, 1};
    CUresult rc = enc(m, CU_TENSOR_MAP_DATA_TYPE_BFLOAT16, rank, const_cast<void*>(ptr), dims, str, box, es, CU_TENSOR_MAP_INTERLEAVE_NONE, sw, pr,
                      CU_TENSOR_MAP_FLOAT_OOB_FILL_NONE);
    (void)rc;
}

}

extern "C" void kernel_launch(void* const* d_in, const int* in_sizes, int n_in, void* d_out, int out_size) {
    (void)in_sizes; (void)n_in; (void)out_size;
    static EncodeFn enc = nullptr;
    static void* scr = nullptr;
    if (!enc) {
        void* fn = nullptr;
        cudaDriverEntryPointQueryResult q;
        cudaGetDriverEntryPoint("cuTensorMapEncodeTiled", &fn, cudaEnableDefault, &q);
        enc = (EncodeFn)fn;
        cudaGetSymbolAddress(&scr, g_scr);
        cudaFuncSetAttribute(fused_kernel, cudaFuncAttributeMaxDynamicSharedMemorySize, SMEM_BYTES);
    }
    Maps maps;
    const uintptr_t ag = (uintptr_t)d_in[9], au = (uintptr_t)d_in[10];
    const auto noprom = CU_TENSOR_MAP_L2_PROMOTION_NONE, prom = CU_TENSOR_MAP_L2_PROMOTION_L2_128B;
    make_map(enc, &maps.rows, 3, d_in[0], {64, SEQ, 16, 1}, {2048, 128, 0}, {64, 16, 4, 1}, CU_TENSOR_MAP_SWIZZLE_128B, noprom);
    make_map(enc, &maps.u, 4, d_in[0], {DM, 4, 16, 32}, {32768, 2048, 131072}, {16, 4, 16, 4}, CU_TENSOR_MAP_SWIZZLE_32B, noprom);
    make_map(enc, &maps.out, 5, d_out, {DM, 4, 8, 2, 32}, {32768, 2048, 16384, 131072}, {16, 4, 2, 2, 4}, CU_TENSOR_MAP_SWIZZLE_NONE, noprom);
    make_map(enc, &maps.wgu, 4, (const void*)(ag < au ? ag : au), {FF, 64, 2, 16}, {FF * 2, ag < au ? au - ag : ag - au, 64 * FF * 2}, {32, 64, 2, 1},
             CU_TENSOR_MAP_SWIZZLE_64B, prom);
    make_map(enc, &maps.wd, 4, d_in[11], {DM, 64, 1, 56}, {2048, 131072, 131072}, {64, 64, 1, 1}, CU_TENSOR_MAP_SWIZZLE_128B, prom);
    Ptrs p;
    p.u = (const __nv_bfloat16*)d_in[0];
    p.logA = (const __nv_bfloat16*)d_in[1];
    p.Aim = (const __nv_bfloat16*)d_in[2];
    p.Cre = (const __nv_bfloat16*)d_in[3];
    p.Cim = (const __nv_bfloat16*)d_in[4];
    p.ldt = (const __nv_bfloat16*)d_in[5];
    p.dsk = (const __nv_bfloat16*)d_in[6];
    p.wr = (const __nv_bfloat16*)d_in[8];
    p.wg = (const __nv_bfloat16*)d_in[9];
    p.wu = (const __nv_bfloat16*)d_in[10];
    p.out = (__nv_bfloat16*)d_out;
    p.scr = (uint32_t*)scr;
    p.up_first = ag < au ? 0 : 4096;
    p.zero = 0;
    fused_kernel<<<NCTA + 2, NTHR, SMEM_BYTES, cudaStreamPerThread>>>(p, maps);
}
```

```cpp
#include <cuda_runtime.h>
#include <cuda_bf16.h>
#include <cuda_fp16.h>
#include <cuda.h>
#include <stdint.h>

namespace {

constexpr int SEQ = 2048, DM = 1024, NMODE = 128, FF = 3584;
constexpr int NCTA = 128, NTHR = 512;
constexpr int GU_CTAS = 112;

constexpr int OFF_X = 0;
constexpr int OFF_RING = 65536;
constexpr int ROW_PITCH = 2064;
constexpr int OFF_ROWS = OFF_RING + 32768;
constexpr int OFF_XS = OFF_RING + 65536;
constexpr int OFF_PRIV = OFF_XS + 8 * ROW_PITCH;
constexpr int PRIV = 8768;
constexpr int PLANE = 2240;
constexpr int OFF_GP = OFF_PRIV + 8 * PRIV;
constexpr int OFF_LC = OFF_GP + 8192;
constexpr int OFF_BAR = OFF_LC + 2048;
constexpr int OFF_MISC = OFF_BAR + 352;
constexpr int OFF_STAMP = OFF_MISC + 288;
constexpr int SMEM_BYTES = OFF_STAMP;

constexpr int B_X = 0, B_FULL = 8, B_EMPTY = 16, B_RECV = 24, B_XS = 28, B_DONE = 29, B_ST = 30, B_ROW = 32, B_WR = 36, B_KG = 37, B_VT = 38, B_PV = 39;

constexpr int T_DENSE = 4416;
constexpr int T_PATCH = T_DENSE + 2176;
constexpr int T_S4 = T_PATCH + 112;
constexpr int T_S8 = T_S4 + 736;
constexpr int REC = 272;

constexpr uint32_t SPIN_LIMIT = 1u << 22;
constexpr int CONV_REGS = 168, FFN_REGS = 144, PROD_REGS = 32;
#define NPRE 4

#define ROW_DELAY 400
#define ROW_PERIOD 560
#define X_DELAY 2500
#define PF_START 3400
#define PF_PERIOD 525
#define WD_EXTRA 110
#define LD_START 5500
#define LD_LAG 520
constexpr int LD_PERIOD = (PF_START + 16 * PF_PERIOD + LD_LAG - LD_START) / 15, LD_SPREAD = 480;

constexpr int S_STAT = 0;
constexpr int S_KEY = S_STAT + 8192;
constexpr int S_SEL = S_KEY + 2048;
constexpr int S_EPOCH = S_SEL + 128;
constexpr int S_H = S_EPOCH + 32;
constexpr int S_Y = S_H + 2 * GU_CTAS * 128;
constexpr int S_END = S_Y + 64 * 1024;
__device__ __align__(1024) uint32_t g_scr[S_END];

struct Ptrs {
    const __nv_bfloat16 *logA, *Aim, *Cre, *Cim, *ldt, *dsk, *u, *wr;
    uint32_t* scr;
    const __nv_bfloat16 *wg, *wu;
    __nv_bfloat16* out;
    uint32_t up_first;
    uint32_t zero;
};
struct Maps {
    CUtensorMap rows, u, out, wgu, wd;
};

__device__ __forceinline__ uint32_t clk() { uint32_t c; asm volatile("mov.u32 %0, %%clock;" : "=r"(c)); return c; }
#define STAMP(i) do { } while (0)
#define GSTAMP(i) do { } while (0)

template <int N> struct IC { static constexpr int value = N; };

__device__ __forceinline__ uint32_t s_u32(const void* p) { return (uint32_t)__cvta_generic_to_shared(p); }
__device__ __forceinline__ void mbar_init(uint32_t b, uint32_t n) {
    asm volatile("mbarrier.init.shared::cta.b64 [%0], %1;" ::"r"(b), "r"(n) : "memory");
}
__device__ __forceinline__ void mbar_expect_tx(uint32_t b, uint32_t bytes) {
    asm volatile("mbarrier.arrive.expect_tx.shared::cta.b64 _, [%0], %1;" ::"r"(b), "r"(bytes) : "memory");
}
__device__ __forceinline__ void mbar_arrive(uint32_t b) {
    asm volatile("mbarrier.arrive.shared::cta.b64 _, [%0];" ::"r"(b) : "memory");
}
__device__ __forceinline__ void mbar_arrive_peer(uint32_t b_cluster) {
    asm volatile("mbarrier.arrive.relaxed.cluster.shared::cluster.b64 _, [%0];" ::"r"(b_cluster) : "memory");
}
__device__ __forceinline__ void mbar_wait(uint32_t b, uint32_t parity) {
    asm volatile("{\n\t.reg .pred p;\nW:\n\tmbarrier.try_wait.parity.shared::cta.b64 p, [%0], %1;\n\t@!p bra W;\n\t}" ::"r"(b), "r"(parity) : "memory");
}
__device__ __forceinline__ void mbar_wait_bounded(uint32_t b, uint32_t parity) {
    asm volatile("{\n\t.reg .pred p;\n\t.reg .u32 c;\n\tmov.u32 c, 0;\n"
                 "W:\n\tmbarrier.try_wait.parity.shared::cta.b64 p, [%0], %1, 4000;\n\t@p bra D;\n\t"
                 "add.u32 c, c, 1;\n\tsetp.lt.u32 p, c, 1048576;\n\t@p bra W;\n\ttrap;\nD:\n\t}"
                 ::"r"(b), "r"(parity) : "memory");
}
__device__ __forceinline__ bool elect_one() {
    uint32_t p;
    asm volatile("{ .reg .pred P; elect.sync _|P, 0xffffffff; selp.u32 %0, 1, 0, P; }" : "=r"(p));
    return p != 0;
}
__device__ __forceinline__ uint32_t mapa(uint32_t a, uint32_t rank) {
    uint32_t r;
    asm("mapa.shared::cluster.u32 %0, %1, %2;" : "=r"(r) : "r"(a), "r"(rank));
    return r;
}
__device__ __forceinline__ void cluster_arrive() { asm volatile("barrier.cluster.arrive.relaxed.aligned;" ::: "memory"); }
__device__ __forceinline__ void cluster_wait() { asm volatile("barrier.cluster.wait.aligned;" ::: "memory"); }
__device__ __forceinline__ void tma_load_3d(uint32_t dst, const CUtensorMap* m, int c1, int c2, uint32_t bar) {
    asm volatile("cp.async.bulk.tensor.3d.shared::cluster.global.mbarrier::complete_tx::bytes [%0], [%1, {%3, %4, %5}], [%2];"
                 ::"r"(dst), "l"(m), "r"(bar), "r"(0), "r"(c1), "r"(c2) : "memory");
}
__device__ __forceinline__ void tma_load_4d(uint32_t dst, const CUtensorMap* m, int c0, int c3, uint32_t bar) {
    uint64_t pol;
    asm("createpolicy.fractional.L2::evict_first.b64 %0, 1.0;" : "=l"(pol));
    asm volatile("cp.async.bulk.tensor.4d.shared::cluster.global.mbarrier::complete_tx::bytes.L2::cache_hint [%0], [%1, {%3, %5, %5, %4}], [%2], %6;"
                 ::"r"(dst), "l"(m), "r"(bar), "r"(c0), "r"(c3), "r"(0), "l"(pol) : "memory");
}
__device__ __forceinline__ void wait_until(uint32_t t) {
    asm volatile("{\n\t.reg .pred p;\n\t.reg .s32 c;\nW:\n\tmov.u32 c, %%clock;\n\tsub.s32 c, %0, c;\n\tshr.s32 c, c, 2;\n\tsetp.gt.s32 p, c, 63;\n\t"
                 "@p nanosleep.u32 c;\n\t@p bra.uni W;\n\t}" ::"r"(t) : "memory");
}
__device__ __forceinline__ void tma_load_4d_both(uint32_t dst, const CUtensorMap* m, int c0, int c3, uint32_t bar) {
    asm volatile("cp.async.bulk.tensor.4d.shared::cluster.global.mbarrier::complete_tx::bytes.multicast::cluster [%0], [%1, {%3, %6, %6, %4}], [%2], %5;"
                 ::"r"(dst), "l"(m), "r"(bar), "r"(c0), "r"(c3), "h"((uint16_t)3), "r"(0) : "memory");
}
__device__ __forceinline__ void bulk_g2s(uint32_t dst, const void* src, uint32_t bytes, uint32_t bar) {
    asm volatile("cp.async.bulk.shared::cluster.global.mbarrier::complete_tx::bytes [%0], [%1], %2, [%3];"
                 ::"r"(dst), "l"(src), "r"(bytes), "r"(bar) : "memory");
}
__device__ __forceinline__ void fence_async() { asm volatile("fence.proxy.async.shared::cta;" ::: "memory"); }
__device__ __forceinline__ void named_sync(int id, int n) { asm volatile("bar.sync %0, %1;" ::"r"(id), "r"(n) : "memory"); }

__device__ __forceinline__ void ldsm4(uint32_t* r, uint32_t a) {
    asm volatile("ldmatrix.sync.aligned.m8n8.x4.shared.b16 {%0,%1,%2,%3}, [%4];"
                 : "=r"(r[0]), "=r"(r[1]), "=r"(r[2]), "=r"(r[3]) : "r"(a));
}
__device__ __forceinline__ void ldsm4t(uint32_t* r, uint32_t a) {
    asm volatile("ldmatrix.sync.aligned.m8n8.x4.trans.shared.b16 {%0,%1,%2,%3}, [%4];"
                 : "=r"(r[0]), "=r"(r[1]), "=r"(r[2]), "=r"(r[3]) : "r"(a));
}
__device__ __forceinline__ void stsm4t(uint32_t a, const uint32_t* r) {
    asm volatile("stmatrix.sync.aligned.m8n8.x4.trans.shared.b16 [%0], {%1,%2,%3,%4};"
                 ::"r"(a), "r"(r[0]), "r"(r[1]), "r"(r[2]), "r"(r[3]) : "memory");
}
__device__ __forceinline__ uint32_t lds32(uint32_t a) { uint32_t v; asm volatile("ld.shared.u32 %0, [%1];" : "=r"(v) : "r"(a)); return v; }
__device__ __forceinline__ uint32_t lds32v(uint32_t a) { uint32_t v; asm volatile("ld.volatile.shared.u32 %0, [%1];" : "=r"(v) : "r"(a)); return v; }
__device__ __forceinline__ uint2 lds64(uint32_t a) { uint2 v; asm volatile("ld.shared.v2.u32 {%0,%1}, [%2];" : "=r"(v.x), "=r"(v.y) : "r"(a)); return v; }
__device__ __forceinline__ uint4 lds128(uint32_t a) {
    uint4 v; asm volatile("ld.shared.v4.u32 {%0,%1,%2,%3}, [%4];" : "=r"(v.x), "=r"(v.y), "=r"(v.z), "=r"(v.w) : "r"(a)); return v;
}
template <int D> __device__ __forceinline__ void sts16x2(uint32_t a, float x) {
    asm volatile("{ .reg .b16 h; cvt.rn.bf16.f32 h, %1; st.shared.b16 [%0], h; st.shared.b16 [%0 + %2], h; }" ::"r"(a), "f"(x), "n"(D) : "memory");
}
__device__ __forceinline__ void sts32(uint32_t a, uint32_t v) { asm volatile("st.shared.u32 [%0], %1;" ::"r"(a), "r"(v) : "memory"); }
__device__ __forceinline__ void sts64(uint32_t a, uint32_t x, uint32_t y) { asm volatile("st.shared.v2.u32 [%0], {%1,%2};" ::"r"(a), "r"(x), "r"(y) : "memory"); }
__device__ __forceinline__ void sts128(uint32_t a, uint32_t x, uint32_t y, uint32_t z, uint32_t w) {
    asm volatile("st.shared.v4.u32 [%0], {%1,%2,%3,%4};" ::"r"(a), "r"(x), "r"(y), "r"(z), "r"(w) : "memory");
}
__device__ __forceinline__ void sts128f(uint32_t a, const float* c) {
    asm volatile("st.shared.v4.f32 [%0], {%1,%2,%3,%4};" ::"r"(a), "f"(c[0]), "f"(c[1]), "f"(c[2]), "f"(c[3]) : "memory");
}
__device__ __forceinline__ uint2 ldg64(const void* p) {
    uint2 v; asm volatile("ld.global.nc.L1::no_allocate.v2.u32 {%0,%1}, [%2];" : "=r"(v.x), "=r"(v.y) : "l"(p)); return v;
}
__device__ __forceinline__ uint32_t ldg16(const void* p) {
    uint16_t v; asm volatile("ld.global.nc.u16 %0, [%1];" : "=h"(v) : "l"(p)); return v;
}
__device__ __forceinline__ uint32_t ld_relaxed_32(const void* p) {
    uint32_t v; asm volatile("ld.relaxed.gpu.global.u32 %0, [%1];" : "=r"(v) : "l"(p) : "memory"); return v;
}
__device__ __forceinline__ uint2 ld_relaxed_64(const void* p) {
    unsigned long long v;
    asm volatile("ld.relaxed.gpu.global.u64 %0, [%1];" : "=l"(v) : "l"(p) : "memory");
    return make_uint2((uint32_t)v, (uint32_t)(v >> 32));
}
__device__ __forceinline__ uint4 ld_relaxed_128(const void* p) {
    uint4 v; asm volatile("ld.relaxed.gpu.global.v4.u32 {%0,%1,%2,%3}, [%4];" : "=r"(v.x), "=r"(v.y), "=r"(v.z), "=r"(v.w) : "l"(p) : "memory"); return v;
}
__device__ __forceinline__ void st_relaxed_32(void* p, uint32_t v) {
    asm volatile("st.relaxed.gpu.global.u32 [%0], %1;" ::"l"(p), "r"(v) : "memory");
}
__device__ __forceinline__ void st_relaxed_128(void* p, uint32_t x, uint32_t y, uint32_t z, uint32_t w) {
    asm volatile("st.relaxed.gpu.global.v4.u32 [%0], {%1,%2,%3,%4};" ::"l"(p), "r"(x), "r"(y), "r"(z), "r"(w) : "memory");
}
__device__ __forceinline__ void st_relaxed_64(void* p, uint32_t x, uint32_t y) {
    asm volatile("st.relaxed.gpu.global.u64 [%0], %1;" ::"l"(p), "l"((unsigned long long)x | ((unsigned long long)y << 32)) : "memory");
}
__device__ __forceinline__ void mma_bf16(float* c, uint32_t a0, uint32_t a1, uint32_t a2, uint32_t a3, uint32_t b0, uint32_t b1) {
    asm("mma.sync.aligned.m16n8k16.row.col.f32.bf16.bf16.f32 {%0,%1,%2,%3}, {%4,%5,%6,%7}, {%8,%9}, {%0,%1,%2,%3};"
                 : "+f"(c[0]), "+f"(c[1]), "+f"(c[2]), "+f"(c[3]) : "r"(a0), "r"(a1), "r"(a2), "r"(a3), "r"(b0), "r"(b1));
}
__device__ __forceinline__ void mma_bf16v(float* c, const uint32_t* a, uint32_t b0, uint32_t b1) {
    asm volatile("mma.sync.aligned.m16n8k16.row.col.f32.bf16.bf16.f32 {%0,%1,%2,%3}, {%4,%5,%6,%7}, {%8,%9}, {%0,%1,%2,%3};"
                 : "+f"(c[0]), "+f"(c[1]), "+f"(c[2]), "+f"(c[3]) : "r"(a[0]), "r"(a[1]), "r"(a[2]), "r"(a[3]), "r"(b0), "r"(b1));
}
__device__ __forceinline__ void mma_bf16_z(float* c, uint32_t a0, uint32_t a1, uint32_t a2, uint32_t a3, uint32_t b0, uint32_t b1) {
    asm("mma.sync.aligned.m16n8k16.row.col.f32.bf16.bf16.f32 {%0,%1,%2,%3}, {%4,%5,%6,%7}, {%8,%9}, {%10,%10,%10,%10};"
        : "=f"(c[0]), "=f"(c[1]), "=f"(c[2]), "=f"(c[3]) : "r"(a0), "r"(a1), "r"(a2), "r"(a3), "r"(b0), "r"(b1), "f"(0.f));
}
__device__ __forceinline__ void mma_f16(float* c, const uint4& a, uint32_t b0, uint32_t b1) {
    asm("mma.sync.aligned.m16n8k16.row.col.f32.f16.f16.f32 {%0,%1,%2,%3}, {%4,%5,%6,%7}, {%8,%9}, {%0,%1,%2,%3};"
                 : "+f"(c[0]), "+f"(c[1]), "+f"(c[2]), "+f"(c[3]) : "r"(a.x), "r"(a.y), "r"(a.z), "r"(a.w), "r"(b0), "r"(b1));
}
__device__ __forceinline__ uint32_t pack_bf16(float lo, float hi) {
    uint32_t r; asm("cvt.rn.bf16x2.f32 %0, %1, %2;" : "=r"(r) : "f"(hi), "f"(lo)); return r;
}
__device__ __forceinline__ uint32_t pack_bf16v(float lo, float hi) {
    uint32_t r; asm("cvt.rn.satfinite.bf16x2.f32 %0, %1, %2;" : "=r"(r) : "f"(hi), "f"(lo)); return r;
}
__device__ __forceinline__ uint32_t pack_f16(float lo, float hi) {
    uint32_t r; asm("cvt.rn.f16x2.f32 %0, %1, %2;" : "=r"(r) : "f"(hi), "f"(lo)); return r;
}
__device__ __forceinline__ float bf_lo(uint32_t v) { return __uint_as_float(v << 16); }
__device__ __forceinline__ float bf_hi(uint32_t v) { return __uint_as_float(v & 0xffff0000u); }
__device__ __forceinline__ float bf_round(float x) { return __uint_as_float(pack_bf16(0.f, x)); }
__device__ __forceinline__ __nv_bfloat162 as_b2(uint32_t x) { return *reinterpret_cast<__nv_bfloat162*>(&x); }
__device__ __forceinline__ uint32_t as_u(__nv_bfloat162 x) { return *reinterpret_cast<uint32_t*>(&x); }
__device__ __forceinline__ uint32_t badd2(uint32_t a, uint32_t b) { uint32_t r; asm("add.rn.bf16x2 %0, %1, %2;" : "=r"(r) : "r"(a), "r"(b)); return r; }
__device__ __forceinline__ float rcpf(float x) { float r; asm("rcp.approx.ftz.f32 %0, %1;" : "=f"(r) : "f"(x)); return r; }
__device__ __forceinline__ float sqrtaf(float x) { float r; asm("sqrt.approx.ftz.f32 %0, %1;" : "=f"(r) : "f"(x)); return r; }
__device__ __forceinline__ float ex2f(float x) { float r; asm("ex2.approx.ftz.f32 %0, %1;" : "=f"(r) : "f"(x)); return r; }
constexpr float L2E = 1.4426950408889634f;
constexpr uint32_t ONES = 0x3f803f80u;

__device__ __forceinline__ uint2 recip2(uint32_t s2) {
    const uint32_t hi = pack_bf16(rcpf(bf_lo(s2)), rcpf(bf_hi(s2)));
    return make_uint2(hi, as_u(__hmul2(__hfma2(__hneg2(as_b2(s2)), as_b2(hi), as_b2(ONES)), as_b2(hi))));
}
__device__ __forceinline__ uint32_t normalize2(uint32_t x, __nv_bfloat162 m, __nv_bfloat162 rh, __nv_bfloat162 rl) {
    const __nv_bfloat162 d = __hsub2(as_b2(x), m);
    return as_u(__hfma2(d, rh, __hmul2(d, rl)));
}

__device__ __forceinline__ uint32_t unorder_key(uint32_t k16) { return k16 ^ ((k16 & 0x8000u) ? 0x8000u : 0xffffu); }

struct cplx { float r, i; };
__device__ __forceinline__ cplx csq(cplx a) { return {a.r * a.r - a.i * a.i, (a.r + a.r) * a.i}; }
__device__ __forceinline__ cplx csq_conj(cplx a) { return {a.r * a.r - a.i * a.i, (-a.r - a.r) * a.i}; }
__device__ __forceinline__ cplx cexpp(float a2, float th) {
    float m = ex2f(a2), s, c;
    __sincosf(th, &s, &c);
    return {m * c, m * s};
}
struct hc { __half2 r, i; };
__device__ __forceinline__ __half2 as_h2(uint32_t x) { return *reinterpret_cast<__half2*>(&x); }
__device__ __forceinline__ uint32_t as_u(__half2 x) { return *reinterpret_cast<uint32_t*>(&x); }
__device__ __forceinline__ hc hmul(hc a, hc b) {
    return {__hfma2(a.r, b.r, __hneg2(__hmul2(a.i, b.i))), __hfma2(a.r, b.i, __hmul2(a.i, b.r))};
}
__device__ __forceinline__ hc hpack(cplx a, cplx b) { return {as_h2(pack_f16(a.r, b.r)), as_h2(pack_f16(a.i, b.i))}; }
__device__ __forceinline__ void st_pair(uint32_t a, hc x, hc y) { sts128(a, as_u(x.r), as_u(x.i), as_u(y.r), as_u(y.i)); }
__device__ __forceinline__ void st_quad(uint32_t a, hc x, hc y) { sts128(a, as_u(x.r), as_u(y.r), as_u(x.i), as_u(y.i)); }

#define KSTAMP(i, dep) do { } while (0)
__device__ __forceinline__ void kgen_mma(float (&acc)[5][4], uint32_t priv, int lane, uint2 la, uint2 aim, uint2 cre, uint2 cim, float dt, uint32_t cs2) {
    const int g = lane >> 2, t = lane & 3;
#pragma unroll
    for (int i = 0; i < 5; i++) { acc[i][0] = acc[i][1] = acc[i][2] = acc[i][3] = 0.f; }
    const uint32_t wr = priv + lane * REC, rd = priv + 2 * t * REC;
    const float ndl = -dt * L2E;
#pragma unroll 1
    for (int ps = 0; ps < 2; ps++) {
        const uint32_t lw = ps ? la.y : la.x, iw = ps ? aim.y : aim.x;
        const uint32_t crw = as_u(__hmul2(as_b2(ps ? cre.y : cre.x), as_b2(cs2))), ciw = as_u(__hmul2(as_b2(ps ? cim.y : cim.x), as_b2(cs2)));
        const uint32_t ap = pack_bf16(ex2f(bf_lo(lw) * L2E), ex2f(bf_hi(lw) * L2E));
        const float a2[2] = {bf_lo(ap) * ndl, bf_hi(ap) * ndl}, th[2] = {bf_lo(iw) * dt, bf_hi(iw) * dt};
        cplx p1[2], p2[2], p4[2], p8[2], p32[2], p64[2], p128[2], p256[2], p512[2];
#pragma unroll
        for (int i = 0; i < 2; i++) {
            p1[i] = cexpp(a2[i], th[i]); p32[i] = cexpp(a2[i] * 32.f, th[i] * -32.f);
            p2[i] = csq(p1[i]); p4[i] = csq(p2[i]); p8[i] = csq_conj(p4[i]);
            p64[i] = csq(p32[i]); p128[i] = csq_conj(p64[i]); p256[i] = csq(p128[i]); p512[i] = csq(p256[i]);
        }
        const hc C = {as_h2(pack_f16(bf_lo(crw), bf_hi(crw))), as_h2(pack_f16(bf_lo(ciw), bf_hi(ciw)))};
        const hc z1 = hpack(p1[0], p1[1]), z2 = hpack(p2[0], p2[1]), z4 = hpack(p4[0], p4[1]);
        const hc y8 = hpack(p8[0], p8[1]), y32 = hpack(p32[0], p32[1]), y64 = hpack(p64[0], p64[1]);
        const hc z128 = hpack(p128[0], p128[1]), z256 = hpack(p256[0], p256[1]), z512 = hpack(p512[0], p512[1]);
        KSTAMP(8 + 3 * ps, z512.r);
        __syncwarp();
        const hc c1 = hmul(C, z1), c2 = hmul(C, z2), c5 = hmul(c1, z4), c6 = hmul(c2, z4);
        st_pair(wr + 160, hmul(c1, z128), hmul(c2, z128));
        st_pair(wr + 128, c1, c2);
        st_pair(wr + 176, hmul(c5, z128), hmul(c6, z128));
        st_pair(wr + 144, c5, c6);
        const hc y16 = hmul(y8, y8), y48 = hmul(y16, y32), y24 = hmul(y16, y8), y40 = hmul(y32, y8), y56 = hmul(y48, y8), y72 = hmul(y64, y8);
        st_quad(wr, {as_h2(0x3c003c00u), as_h2(0u)}, y8);
        st_quad(wr + 80, hmul(y64, y16), hmul(y64, y24));
        st_quad(wr + 16, y16, y24);
        st_quad(wr + 96, hmul(y64, y32), hmul(y64, y40));
        st_quad(wr + 32, y32, y40);
        st_quad(wr + 112, hmul(y64, y48), hmul(y64, y56));
        st_quad(wr + 48, y48, y56);
        st_quad(wr + 64, y64, y72);
        const hc z258 = hmul(z256, z2);
        st_pair(wr + 192, hmul(z256, z1), z258);
        st_pair(wr + 224, z2, hmul(z512, z4));
        st_pair(wr + 240, z2, hmul(z512, z512));
        st_pair(wr + 208, z258, z512);
        KSTAMP(9 + 3 * ps, z512.r);
        __syncwarp();
#pragma unroll
        for (int k2 = 0; k2 < 4; k2++) {
#pragma unroll
            for (int s = 0; s < 2; s++) {
                const uint32_t o = rd + k2 * 8 * REC + s * REC;
                const uint4 A = lds128(o + 16 * g);
                const uint2 h = lds64(o + 128 + 8 * g);
                const uint4 M = lds128(o + 192 + 16 * (g & 1)), N = lds128(o + 224 + 8 * (g & 2));
                const hc H0 = {as_h2(h.x), as_h2(h.y)};
                const hc H1 = hmul(H0, {as_h2(N.x), as_h2(N.y)}), H2 = hmul(H0, {as_h2(M.x), as_h2(M.y)});
                const hc H3 = hmul(H2, {as_h2(M.z), as_h2(M.w)}), H4 = hmul(H3, {as_h2(N.z), as_h2(N.w)});
                mma_f16(acc[0], A, h.x, h.y);
                mma_f16(acc[1], A, as_u(H1.r), as_u(H1.i));
                mma_f16(acc[2], A, as_u(H2.r), as_u(H2.i));
                mma_f16(acc[3], A, as_u(H3.r), as_u(H3.i));
                mma_f16(acc[4], A, as_u(H4.r), as_u(H4.i));
            }
        }
        KSTAMP(10 + 3 * ps, z512.r);
    }
}

__device__ __forceinline__ void kgen_tables(const float (&acc)[5][4], uint32_t priv, int lane, float scale, float k0) {
    const int g = lane >> 2, t0 = lane & 1, t1 = (lane >> 1) & 1;
    __syncwarp();
    sts128(priv + 16 * lane + (lane < 17 ? T_PATCH - 48 : T_S4 + 608 - 272), 0, 0, 0, 0);
    if (lane < 20) sts128(priv + 16 * lane + (lane < 8 ? 0 : lane < 16 ? PLANE - 128 : T_DENSE - 256), 0, 0, 0, 0);
    uint32_t w2[2], w3[2], w4[2], ab[2], W[2], pv[2];
#pragma unroll
    for (int hf = 0; hf < 2; hf++) {
        const float k1 = acc[0][2 * hf] * scale, k2 = acc[0][2 * hf + 1] * scale, k3 = acc[1][2 * hf] * scale, k4 = acc[1][2 * hf + 1] * scale;
        w2[hf] = pack_bf16(k2, k1); w3[hf] = pack_bf16(k3, k2); w4[hf] = pack_bf16(k4, k3);
        ab[hf] = pack_bf16(acc[2][2 * hf + 1] * scale, acc[2][2 * hf] * scale);
        W[hf] = __byte_perm(w4[hf], ab[hf], 0x5410);
    }
    pv[1] = __shfl_xor_sync(0xffffffffu, t0 ? W[0] : W[1], 1);
    pv[0] = __shfl_sync(0xffffffffu, t0 ? W[1] : W[0], t0 ? lane - 1 : lane < 4 ? 31 - lane : lane - 3);
    const uint32_t kk = pack_bf16(k0, 0.f);
    if (lane == 0) pv[0] = __byte_perm(kk, pv[0], 0x5410);
    const uint32_t pd = priv + T_DENSE + 64 + 512 * t1 + 64 * g + 16 * t0;
#pragma unroll
    for (int hf = 0; hf < 2; hf++) {
        sts128(pd + 32 * hf, __byte_perm(w2[hf], pv[hf], 0x5432), w2[hf], w3[hf], w4[hf]);
        sts128(pd + 32 * hf + 1024, __byte_perm(pv[hf], 0, 0x3232), __byte_perm(ab[hf], pv[hf], 0x7632), ab[hf], __byte_perm(ab[hf], 0, 0x1010));
    }
    __syncwarp();
    if (lane == 31) {
        const uint32_t aa = __byte_perm(ab[1], 0, 0x1010);
        sts32(priv + T_DENSE + 60, kk);
        sts128(priv + T_PATCH - 64, aa, aa, aa << 16, 0u);
    }
}
__device__ __forceinline__ void kgen_tables2(const float (&acc)[5][4], uint32_t priv, int lane, float scale) {
    const int g = lane >> 2, t0 = lane & 1, t1 = (lane >> 1) & 1;
    const uint32_t p4 = priv + T_S4 + 16 * (6 + g + 8 * t1) + 4 * (t0 ^ 1), p8 = priv + T_S8 + 8 * (6 + g + 8 * t1 + 32 * t0);
#pragma unroll
    for (int i = 0; i < 4; i++) {
        sts16x2<18>(p4 + 256 * (i & 1) + 8 * (i >> 1), acc[3][i] * scale);
        sts16x2<10>(p8 + 128 * (i & 1) + 4 * (i >> 1), acc[4][i] * scale);
    }
    if (lane == 31) {
        const uint32_t c3 = pack_bf16(acc[3][3] * scale, 0.f);
        sts128(priv + T_PATCH + 48, c3, c3 * 0x10001u, c3 << 16, 0u);
    }
    __syncwarp();
}

__device__ __forceinline__ void ld_frag(uint32_t (&T)[4], uint32_t q) { T[0] = lds32(q); T[1] = lds32(q + 32); T[2] = lds32(q - 32); T[3] = lds32v(q); }
__device__ __forceinline__ void ld_swap(uint32_t (&T)[4], uint32_t q) { T[2] = lds32v(q); T[3] = lds32v(q + 32); T[0] = lds32v(q - 32); T[1] = lds32v(q); }
__device__ __forceinline__ void add_frag(uint32_t (&S)[4], const uint32_t (&E)[4], const uint32_t (&O)[4]) {
    S[0] = badd2(E[0], O[1]); S[1] = badd2(E[1], O[3]); S[2] = badd2(E[2], O[0]); S[3] = badd2(E[3], O[2]);
}
__device__ __forceinline__ void mma4(float* c, const uint32_t (&a)[4], uint32_t b0, uint32_t b1, bool first = false) {
    if (first) mma_bf16_z(c, a[0], a[1], a[2], a[3], b0, b1);
    else mma_bf16(c, a[0], a[1], a[2], a[3], b0, b1);
}
template <bool FIRST>
__device__ __forceinline__ void dense_step(float (&acc)[16][4], float (&B)[8][4], uint32_t (&T0)[4], uint32_t (&T1)[4], uint32_t (&R)[8][4],
                                           uint32_t pq, uint32_t va) {
    uint32_t T2[4], T3[4], S[4], s[8][2];
#pragma unroll
    for (int i = NPRE; i < 8; i++) ldsm4(R[i], va + i * 256);
    ld_frag(T2, pq + 1024); ld_swap(T3, pq + 1536);
    add_frag(S, T0, T1);
#pragma unroll
    for (int i = 0; i < 8; i++) {
        s[i][0] = badd2(R[i][0], R[i][3]); s[i][1] = badd2(R[i][1], R[i][2]);
        mma4(acc[2 * i], T0, R[i][0], R[i][1], FIRST);
        mma4(B[i], T1, R[i][2], R[i][3], FIRST);
        mma4(acc[2 * i + 1], S, s[i][0], s[i][1], FIRST);
    }
    ld_frag(T0, pq - 64); ld_swap(T1, pq + 448);
    add_frag(S, T2, T3);
#pragma unroll
    for (int i = 0; i < 7; i++) {
        if (!FIRST || i) mma4(acc[2 * i + 2], T2, R[i][0], R[i][1]);
        mma4(B[i + 1], T3, R[i][2], R[i][3]);
        mma4(acc[2 * i + 3], S, s[i][0], s[i][1]);
        if (i < NPRE) ldsm4(R[i], va + 16 + i * 256);
    }
}
template <class Wait, class After>
__device__ __forceinline__ void dense_phase(float (&acc)[16][4], uint32_t priv, int lane, Wait wait_for_tokens, After after_loop) {
    const int m = lane >> 3, r = lane & 7;
    const uint32_t pb = priv + T_DENSE + 4 * (15 + (lane >> 2) - 2 * (lane & 3));
    const uint32_t v8 = priv + 128 * (m >> 1) + 16 * r;
    float B[8][4];
    uint32_t T0[4], T1[4], R[8][4];
    uint32_t pq = pb + 512, va = v8 + PLANE * ((m ^ (m >> 1)) & 1);
    ld_frag(T0, pq); ld_swap(T1, pq + 512);
    wait_for_tokens();
#pragma unroll
    for (int i = 0; i < NPRE; i++) ldsm4(R[i], va + i * 256);
    dense_step<true>(acc, B, T0, T1, R, pq, va);
#pragma unroll 1
    do {
        pq -= 64; va += 16;
        dense_step<false>(acc, B, T0, T1, R, pq, va);
    } while (pq != pb + 64);
    after_loop();
    KSTAMP(14, as_h2(0u));
    const uint32_t pp = pb + T_PATCH - T_DENSE - 24;
    uint32_t N0[4], N1[4];
    ld_swap(T1, pb); ld_frag(N0, pp); ld_swap(N1, pp);
#pragma unroll
    for (int i = NPRE; i < 8; i++) ldsm4(R[i], va + 16 + i * 256);
#pragma unroll
    for (int i = 0; i < 8; i++)
#pragma unroll
        for (int j = 0; j < 4; j++) {
            acc[2 * i + 1][j] = (acc[2 * i + 1][j] - acc[2 * i][j]) - B[i][j];
            if (i) acc[2 * i][j] += B[i - 1][j];
        }
#pragma unroll
    for (int i = 0; i < 8; i++) {
        mma4(acc[2 * i], T0, R[i][0], R[i][1]);
        mma4(acc[2 * i + 1], T1, R[i][2], R[i][3]);
        if (i >= 4) {
            mma4(acc[2 * i], N0, R[i - 4][0], R[i - 4][1]);
            mma4(acc[2 * i + 1], N1, R[i - 4][2], R[i - 4][3]);
        }
    }
    const uint32_t b = v8 + PLANE + 112;
    const uint32_t bz = (m & 1) ? priv : b, bm = (m & 1) ? b : b + 512;
    const uint32_t M[4] = {lds32(pb + 4 * 520), lds32(pb + 4 * 528), lds32v(pp + 32), lds32(pp + 64)};
#pragma unroll
    for (int i = 0; i < 6; i++) {
        uint32_t V[4];
        ldsm4(V, i < 2 ? bz + ((m & 1) ? 0 : i * 256) : bm + (i - 2) * 256);
        mma4(acc[2 * i + 4], M, V[0], V[1]);
        mma4(acc[2 * i + 5], M, V[2], V[3]);
    }
}

__device__ __forceinline__ uint32_t ones2(int c, int lo, int n) {
    return (((uint32_t)(c - lo) < (uint32_t)n) ? 0x3f80u : 0u) | (((uint32_t)(c + 1 - lo) < (uint32_t)n) ? 0x3f800000u : 0u);
}
template <int L1, int N1, int L2, int N2, int D>
__device__ __forceinline__ void box_ones(uint32_t dst, int d) { sts128(dst, ones2(d, L1, N1), ones2(d, L2, N2), ones2(d + D, L1, N1), ones2(d + D, L2, N2)); }
__device__ __forceinline__ uint32_t tok_at(int T) { return PLANE * ((T >> 3) & 1) + 16 * ((T >> 4) + 8) + 2 * (T & 7); }
__device__ __forceinline__ float left_col(float cur, float prev, int lane) {
    return __shfl_sync(0xffffffffu, (lane & 3) == 3 ? prev : cur, lane + 3, 4);
}
struct Tails {
    uint4 q4, q8, B4[5], ad;
    uint2 B8[8];
    uint32_t W[2][4], A[2][2][4];
    float p1, p3, p8;
    static __host__ __device__ constexpr bool is8(int k) { return k >= 4 && (k & 1); }
    static __host__ __device__ constexpr int grp(int k) { return k < 4 ? k : (k - 4) / 2 + (is8(k) ? 0 : 4); }
    __device__ __forceinline__ void load(int k, uint32_t priv) {
        uint32_t* w = W[k & 1];
        const uint32_t o = priv + 128 * grp(k);
        if (is8(k)) {
            const uint2 vy = lds64(o + ad.w), vx = lds64(o + ad.z);
            w[0] = vy.x; w[1] = vy.y; w[2] = vx.x; w[3] = vx.y;
        } else { w[0] = lds32(o + ad.y); w[1] = lds32(o + ad.x + 16); w[2] = lds32(o + ad.x); w[3] = lds32v(o + ad.y); }
    }
    __device__ __forceinline__ void box(int k, int lane) {
        const uint32_t* w = W[k & 1];
        const uint4 q = is8(k) ? q8 : q4;
        uint32_t (&a)[2][4] = A[k & 1];
        float X[4], Y[4];
        mma_bf16_z(Y, q.x, q.y, q.z, q.w, w[0], w[1]);
        mma_bf16_z(X, q.x, q.y, q.z, q.w, w[2], w[3]);
        a[0][0] = pack_bf16(X[0], X[1]); a[0][1] = pack_bf16(Y[0], Y[1]);
        if (is8(k)) {
            a[0][2] = pack_bf16(left_col(Y[3], p8, lane), Y[2]); a[0][3] = pack_bf16(X[2], X[3]);
            p8 = Y[3];
        } else {
            a[0][2] = pack_bf16(X[2], X[3]); a[0][3] = pack_bf16(Y[2], Y[3]);
            a[1][0] = pack_bf16(left_col(Y[1], p1, lane), Y[0]); a[1][1] = pack_bf16v(X[0], X[1]);
            a[1][2] = pack_bf16(left_col(Y[3], p3, lane), Y[2]); a[1][3] = pack_bf16v(X[2], X[3]);
            p1 = Y[1]; p3 = Y[3];
        }
    }
    __device__ __forceinline__ void taps(int k, float (&acc)[16][4]) {
        const int G = grp(k);
        if (is8(k)) {
#pragma unroll
            for (int b = 0; b < 8; b++) if (G + 8 + b < 16) mma4(acc[G + 8 + b], A[k & 1][0], B8[b].x, B8[b].y);
        } else {
#pragma unroll
            for (int b = 0; b < 5; b++) if (G + 4 + b < 16) mma4(acc[G + 4 + b], A[k & 1][0], B4[b].x, B4[b].y);
#pragma unroll
            for (int b = 0; b < 5; b++) if (G + 4 + b < 16) mma4(acc[G + 4 + b], A[k & 1][1], B4[b].z, B4[b].w);
        }
    }
    __device__ __forceinline__ void start(uint32_t lc, uint32_t priv, uint32_t tap, int lane) {
        ad = lds128(lc + 1024); q4 = lds128(lc); q8 = lds128(lc + 512);
        p1 = p3 = p8 = 0.f;
        load(0, priv); load(1, priv);
#pragma unroll
        for (int i = 0; i < 5; i++) B4[i] = lds128(priv + T_S4 + 128 * i + 2 * tap);
        box(0, lane);
    }
    template <int K0, int K1>
    __device__ __forceinline__ void run(float (&acc)[16][4], uint32_t priv, uint32_t tap, int lane) {
#pragma unroll
        for (int k = K0; k < K1; k++) {
            if (k + 2 < 20) load(k + 2, priv);
            if (k == 4) {
#pragma unroll
                for (int i = 0; i < 8; i++) B8[i] = lds64(priv + T_S8 + 64 * i + tap);
            }
            if (k + 1 < 20) box(k + 1, lane);
            taps(k, acc);
        }
    }
};
__device__ __forceinline__ void lane_consts(uint32_t dst, int unit, int lane) {
    const int g = lane >> 2, t = lane & 3, m = lane >> 3, r = lane & 7;
    if (unit == 0) box_ones<0, 5, 5, 3, 8>(dst, 2 * t - g);
    else if (unit == 1) box_ones<1, 7, 0, 9, 2>(dst, 4 * t - g);
    else if (unit == 2) sts128(dst, tok_at(16 * g - 10 + 2 * t), tok_at(16 * g - 2 + 2 * t), tok_at(16 * g - 12 + 4 * t), tok_at(16 * g - 4 + 4 * t));
    else {
        const uint32_t low = 64 * (t >> 1) + 32 * (g & 1) + 16 * (t & 1), hi = (lane & 24) + (lane & 16);
        sts128(dst, 128 * hi + low, 512 * (4 * (r & 2) + 2 * m + (r & 1)) + 16 * ((r >> 2) ^ (2 * (r & 3))), 32 * hi + low, 8 * (6 + g - 2 * t));
    }
}

__device__ __forceinline__ uint32_t mean_std(float mu, float var) { return pack_bf16(mu, sqrtaf(bf_round(bf_round(var) + 1e-5f))); }
__device__ __noinline__ uint2 ln_centred(uint32_t sb, float mu) {
    const int lane = threadIdx.x & 31;
    uint32_t ms = 0;
    float res = 0.f, ri = 0.f;
#pragma unroll 1
    for (int mode = 0; mode < 2; mode++) {
#pragma unroll 1
        for (int rr = 0; rr < 16; rr++) {
            const float c0 = __shfl_sync(0xffffffffu, mu, rr), rj = __shfl_sync(0xffffffffu, ri, rr);
            float c = 0.f;
#pragma unroll 1
            for (int k = 0; k < 16; k++) {
                const uint32_t q = lds32(sb + OFF_ROWS + k * 2048 + rr * 128 + ((lane * 4) ^ ((rr & 7) << 4))), wq = lds32(sb + OFF_GP + k * 128 + lane * 4);
                const float d0 = bf_lo(q) - c0, d1 = bf_hi(q) - c0;
                if (mode) c = fmaf(bf_round(bf_round(d0) * rj), bf_lo(wq), fmaf(bf_round(bf_round(d1) * rj), bf_hi(wq), c));
                else c = fmaf(d0, d0, fmaf(d1, d1, c));
            }
#pragma unroll 1
            for (int o = 16; o; o >>= 1) c += __shfl_xor_sync(0xffffffffu, c, o);
            if ((lane & 15) == rr) res = c;
        }
        if (mode == 0) { ms = mean_std(mu, res * (1.f / DM)); mu = bf_lo(ms); ri = rcpf(bf_hi(ms)); }
    }
    named_sync(1, 128);
    return make_uint2(ms, __float_as_uint(res));
}

__device__ __forceinline__ void router_cta(uint32_t* scr, uint32_t sb, uint32_t zero, int tid, int warp) {
    const int lane = tid & 31;
    const uint32_t cand = sb + 128;
    const uint32_t epoch = ld_relaxed_32(scr + S_EPOCH);
    if (tid < 128) st_relaxed_32(scr + S_SEL + tid, 0u);
    if (tid == 0) sts32(sb + 64, cand);
    sts128(cand + 16 * tid, 0, 0, 0, 0);
    asm volatile("fence.acq_rel.gpu;" ::: "memory");
    const uint32_t tag = (epoch + 1u) | 0x8000u;
    STAMP(0); GSTAMP(1);
    uint32_t* const psel = scr + S_SEL + 32 * (lane & 3);
    const uint32_t cnt = sb + 64 + (tid & zero);
    uint32_t it = 0;
    uint4 q;
#pragma unroll 1
    do {
        q = ld_relaxed_128(scr + S_KEY + 4 * tid);
        if (++it > SPIN_LIMIT) __trap();
    } while (!__all_sync(0xffffffffu, (((q.x ^ tag) | (q.y ^ tag) | (q.z ^ tag) | (q.w ^ tag)) & 0xffffu) == 0));
    STAMP(2);
    uint32_t key[4] = {q.x, q.y, q.z, q.w};
#pragma unroll
    for (int j = 0; j < 4; j++) key[j] = ((key[j] ^ ((uint32_t)((int)key[j] >> 31) | 0x80000000u)) & 0xffff0000u) | (0xffffu - (uint32_t)(4 * tid + j));
    const uint32_t gm = __reduce_max_sync(0xffffffffu, max(max(key[0], key[1]), max(key[2], key[3])));
    sts32(sb + 4 * warp, gm);
    __syncthreads();
    const uint2 pr = lds64(sb + 8 * (lane & 7));
    const uint32_t tau = __reduce_min_sync(0xffffffffu, max(pr.x, pr.y));
    asm volatile("{\n\t.reg .pred p<4>;\n\t.reg .u32 a<4>;\n\t"
                 "setp.ge.u32 p0, %0, %4;\n\tsetp.ge.u32 p1, %1, %4;\n\tsetp.ge.u32 p2, %2, %4;\n\tsetp.ge.u32 p3, %3, %4;\n\t"
                 "@p0 atom.shared.add.u32 a0, [%5], 4;\n\t@p1 atom.shared.add.u32 a1, [%5], 4;\n\t"
                 "@p2 atom.shared.add.u32 a2, [%5], 4;\n\t@p3 atom.shared.add.u32 a3, [%5], 4;\n\t"
                 "@p0 st.shared.u32 [a0], %0;\n\t@p1 st.shared.u32 [a1], %1;\n\t@p2 st.shared.u32 [a2], %2;\n\t@p3 st.shared.u32 [a3], %3;\n\t}"
                 ::"r"(key[0]), "r"(key[1]), "r"(key[2]), "r"(key[3]), "r"(tau), "r"(cnt) : "memory");
    __syncthreads();
    STAMP(6);
    const uint32_t c0 = lds32v(cand + 4 * lane);
    uint2 k = lds64(cand + 8 * warp);
    const uint32_t end = __shfl_sync(0xffffffffu, lds32v(sb + 64), 0);
    uint32_t i = cand + 8 * warp;
#pragma unroll 1
    do {
        uint32_t r0 = __popc(__ballot_sync(0xffffffffu, c0 > k.x)), r1 = __popc(__ballot_sync(0xffffffffu, c0 > k.y));
#pragma unroll 1
        for (uint32_t j = cand + 128; j < end; j += 128) {
            const uint32_t c = lds32(j + 4 * lane);
            r0 += __popc(__ballot_sync(0xffffffffu, c > k.x)); r1 += __popc(__ballot_sync(0xffffffffu, c > k.y));
        }
        const uint32_t rk = (lane & 4) ? r1 : r0;
        if (rk < 8 && lane < 8) st_relaxed_64(psel + 2 * rk, (lane & 4) ? k.y : k.x, tag);
        i += 128;
        k = lds64(i);
    } while (i < end);
    STAMP(4); GSTAMP(5);
    if (tid == 0) st_relaxed_32(scr + S_EPOCH, epoch + 1u);
}

__global__ void __cluster_dims__(2, 1, 1) __launch_bounds__(NTHR, 1)
fused_kernel(const __grid_constant__ Ptrs p, const __grid_constant__ Maps maps) {
    extern __shared__ __align__(1024) unsigned char smem[];
    const uint32_t sb = s_u32(smem);
    const int tid = threadIdx.x, lane = tid & 31;
    const int warp = __shfl_sync(0xffffffffu, tid >> 5, 0);
    const int b = blockIdx.x, h = b & 1, cl = b >> 1;
    const uint32_t bar0 = sb + OFF_BAR;
    const int m = lane >> 3, r = lane & 7;
    if (b >= NCTA) {
        if (b == NCTA) router_cta(p.scr, sb, p.zero, tid, warp);
        return;
    }
    if (warp < 8) {
        const int w = warp, dch = 8 * b + w;
        STAMP(0);
        const int po = dch * NMODE + 4 * lane;
        const uint2 la = ldg64(p.logA + po), aim = ldg64(p.Aim + po), cre = ldg64(p.Cre + po), cim = ldg64(p.Cim + po);
        const uint32_t ldt16 = ldg16(p.ldt + dch), dsk16 = ldg16(p.dsk + dch);
        cluster_arrive();
        asm volatile("setmaxnreg.inc.sync.aligned.u32 %0;" ::"n"(CONV_REGS));
        const uint32_t priv = sb + OFF_PRIV + w * PRIV;
        const int g = lane >> 2, t = lane & 3;
        float kacc[5][4], kscale;
        {
            const uint32_t m2 = as_u(__hmax2(__hmax2(__habs2(as_b2(cre.x)), __habs2(as_b2(cre.y))), __hmax2(__habs2(as_b2(cim.x)), __habs2(as_b2(cim.y)))));
            const uint32_t eb = min(max(__reduce_max_sync(0xffffffffu, max(m2 << 16, m2)) >> 23, 1u), 252u);
            const float dt = bf_round(ex2f(bf_lo(ldt16) * L2E));
            STAMP(1);
            kgen_mma(kacc, priv, lane, la, aim, cre, cim, dt, (253u - eb) * 0x00800080u);
            STAMP(2);
            cluster_wait();
            __syncwarp();
            if (elect_one()) mbar_arrive(bar0 + 8 * B_KG);
            float s0[4];
            mma_bf16_z(s0, ONES, ONES, ONES, ONES, cre.x, cre.y);
            float k0 = s0[0] + s0[1];
            k0 += __shfl_xor_sync(0xffffffffu, k0, 1);
            k0 += __shfl_xor_sync(0xffffffffu, k0, 2);
            kscale = (dt + dt) * __uint_as_float((eb + 1u) << 23);
            kgen_tables(kacc, priv, lane, kscale, fmaf(k0, dt + dt, bf_lo(dsk16) + 1.f));
        }
        STAMP(3);
        kgen_tables2(kacc, priv, lane, kscale);
        STAMP(4);
        float acc[16][4];
        dense_phase(acc, priv, lane, [&]() {
            mbar_wait(bar0 + 8 * B_VT, 0);
            STAMP(6);
        }, [&]() { mbar_wait(bar0 + 8 * B_PV, 0); });
        STAMP(7);
        const uint32_t sd = sb + OFF_X + 512 * (8 * h + w) + 16 * (lane ^ (2 * (w & 1) + 4 * h));
        const uint32_t sd0 = mapa(sd + 8192, 0), sd1 = mapa(sd, 1);
        auto send = [&](auto PT) {
            constexpr int pt = decltype(PT)::value;
#pragma unroll
            for (int i = 0; i < 2; i++) {
                const float* c0 = acc[4 * pt + 2 * i];
                const float* c1 = acc[4 * pt + 2 * i + 1];
                asm volatile("st.async.weak.shared::cluster.mbarrier::complete_tx::bytes.v4.b32 [%0 + %6], {%1,%2,%3,%4}, [%5];"
                             ::"r"(i ? sd1 : sd0), "r"(pack_bf16(c0[0], c0[1])), "r"(pack_bf16(c0[2], c0[3])), "r"(pack_bf16(c1[0], c1[1])),
                               "r"(pack_bf16(c1[2], c1[3])), "r"(mapa(bar0 + 8 * (B_RECV + pt), i)), "n"(16384 * pt) : "memory");
            }
        };
        const uint4 lc = lds128(sb + OFF_LC + 1536 + 16 * lane);
        const uint32_t stg = (priv + T_DENSE + 63) & ~127u, so = stg + lc.z;
        const uint32_t xa = sb + OFF_X + 16384 * (w >> 2) + 8192 * h + 256 * (w & 3) + lc.x;
        const uint32_t sa = sb + OFF_X + 16384 * (w >> 2) + 8192 * (h ^ 1) + 128 * (w & 3) + lc.y;
        auto finish = [&](int ph) {
            const int box = 4 * ph + 2 * (w >> 2) + h;
            uint4 x[4];
            uint32_t s[4][4];
#pragma unroll
            for (int i = 0; i < 4; i++) x[i] = lds128((xa ^ (8 * (i & 2))) + 32768 * ph + 2048 * (i & 1) + 64 * (i & 2));
            mbar_wait(bar0 + 8 * (B_RECV + 2 * ph + (w >> 2)), 0);
            const uint32_t routed = __shfl_sync(0xffffffffu, lds32(sb + OFF_MISC + 4), 0);
#pragma unroll
            for (int i = 0; i < 4; i++) ldsm4t(s[i], (sa ^ (32 * i)) + 32768 * ph);
#pragma unroll
            for (int i = 0; i < 4; i++) { s[i][0] = badd2(x[i].x, s[i][0]); s[i][1] = badd2(x[i].y, s[i][1]); s[i][2] = badd2(x[i].z, s[i][2]); s[i][3] = badd2(x[i].w, s[i][3]); }
            if ((routed >> (4 * box + (w & 3))) & 1) {
                const uint32_t tk = 256 * box + 128 * (g >> 2) + 32 * (t >> 1) + 16 * (g & 1) + 4 * (g & 2) + 2 * (w & 3);
                const uint32_t mk[2] = {lds32(sb + OFF_MISC + 32 + 4 * (tk >> 5)) >> (tk & 31), lds32(sb + OFF_MISC + 40 + 4 * (tk >> 5)) >> (tk & 31)};
                __nv_bfloat16* o = p.out + (size_t)tk * DM + 16 * cl + 8 * (t & 1);
#pragma unroll
                for (int i = 0; i < 4; i++)
                    asm volatile("{\n\t.reg .pred p;\n\tsetp.eq.u32 p, %6, 0;\n\t@!p st.shared.v4.u32 [%1], {%2,%3,%4,%5};\n\t@p st.global.v4.u32 [%0], {%2,%3,%4,%5};\n\t}"
                                 ::"l"(o + (64 * (i & 1) + (i >> 1)) * DM), "r"((xa ^ (8 * (i & 2))) + 32768 * ph + 2048 * (i & 1) + 64 * (i & 2)),
                                   "r"(s[i][0]), "r"(s[i][1]), "r"(s[i][2]), "r"(s[i][3]), "r"(mk[i & 1] & (1u << (i >> 1))) : "memory");
            } else {
#pragma unroll
                for (int i = 0; i < 4; i++) sts128(so - 2048 * ph + 512 * (i & 1) + 64 * (i & 2), s[i][0], s[i][1], s[i][2], s[i][3]);
                fence_async();
                __syncwarp();
                if (elect_one()) {
                    asm volatile("cp.async.bulk.tensor.5d.global.shared::cta.bulk_group [%0, {%2, %5, %3, %5, %4}], [%1];"
                                 ::"l"(&maps.out), "r"(stg - 2048 * ph), "r"(16 * cl), "r"(2 * (w & 3)), "r"(4 * box), "r"(0) : "memory");
                }
            }
        };
        Tails tl;
        tl.start(sb + OFF_LC + 16 * lane, priv, lc.w, lane);
        send(IC<0>());
        tl.run<0, 4>(acc, priv, lc.w, lane);
        send(IC<1>());
        STAMP(8);
        if (w < 4) finish(0);
        tl.run<4, 12>(acc, priv, lc.w, lane);
        send(IC<2>());
        STAMP(9);
        if (w >= 4) finish(0);
        tl.run<12, 20>(acc, priv, lc.w, lane);
        STAMP(11);
        send(IC<3>());
        finish(1);
        STAMP(12);
        __syncwarp();
        if (elect_one()) mbar_arrive(bar0 + 8 * B_ST);
        asm volatile("cp.async.bulk.commit_group;" ::: "memory");
        asm volatile("cp.async.bulk.wait_group.read 0;" ::: "memory");
        STAMP(13); GSTAMP(15);
    } else if (warp < 12) {
        const int a = warp - 8, at = 32 * a + lane, g = lane >> 2, t = lane & 3;
        STAMP(0);
        if (elect_one()) {
            if (a < 3) {
#pragma unroll
                for (int i = 0; i < 8; i++) mbar_init(bar0 + 64 * a + 8 * i, a == 2 ? 4 : 1);
                mbar_init(bar0 + 8 * (B_KG + a), a ? 4 : 8);
            } else {
#pragma unroll
                for (int i = 0; i < 7; i++) mbar_init(bar0 + 8 * (B_RECV + i), (0x8411122u >> (4 * i)) & 15);
            }
            asm volatile("fence.mbarrier_init.release.cluster;" ::: "memory");
            fence_async();
        }
        __syncwarp();
        if (lane < (a == 0 ? 8 : a == 3 ? 5 : 0)) mbar_expect_tx(bar0 + 64 * a + 8 * lane, a == 3 && lane == 4 ? 16384 : 8192);
        __syncwarp();
        cluster_arrive();
        asm volatile("setmaxnreg.inc.sync.aligned.u32 %0;" ::"n"(FFN_REGS));
        const uint32_t epoch = ld_relaxed_32(p.scr + S_EPOCH);
        uint32_t* const pst = p.scr + S_STAT + 2048 * a + 16 * b + 2 * r + m;
        uint32_t* const pky = p.scr + S_KEY + 16 * b + at;
        if (at < 16) st_relaxed_32(pky, 0u);
        uint32_t* const py = p.scr + S_Y + 1024 * ((cl & ~3) + a) + 128 * (b & 7) + 32 * t + 4 * g;
        const uint32_t gp = sb + OFF_GP;
        sts32(gp + 2048 + 4 * lane, ONES);
        lane_consts(sb + OFF_LC + 16 * at, a, lane);
        cluster_wait();
        STAMP(1);
        if (lane < 16) st_relaxed_32(pst, epoch << 31);
        mbar_wait(bar0 + 8 * B_WR, 0);
        float wsum;
        {
            const uint4 q = lds128(gp + 16 * at);
            wsum = ((bf_lo(q.x) + bf_hi(q.x)) + (bf_lo(q.y) + bf_hi(q.y))) + ((bf_lo(q.z) + bf_hi(q.z)) + (bf_lo(q.w) + bf_hi(q.w)));
#pragma unroll
            for (int o = 16; o; o >>= 1) wsum += __shfl_xor_sync(0xffffffffu, wsum, o);
            sts32(gp + 2176 + 4 * a, __float_as_uint(wsum));
        }
        const uint32_t hsel = (epoch & 1) * (GU_CTAS * 128), want = (epoch & 1) ? 0u : 0x80008000u;
        const uint32_t tbit = ~epoch << 31, ktag = ((epoch + 1u) | 0x8000u) & 0xffffu;
        if (a == 0) sts64(sb + OFF_MISC + 32 + 8 * lane, 0u, 0u);
        if (b < GU_CTAS) st_relaxed_32(p.scr + S_H + (GU_CTAS * 128 - hsel) + b * 128 + at, 0u);
        {
            uint32_t ra[4], rs;
#pragma unroll
            for (int i = 0; i < 4; i++) {
                ra[i] = (m & 1) ? (r == 1 ? gp + 128 * a + 32 * i + 16 * (m >> 1) : gp + 2048) : sb + OFF_ROWS + 2048 * a + 128 * r + (((2 * i + (m >> 1)) ^ r) << 4);
            }
            rs = (m & 1) ? (r == 1 ? 512 : 0) : 8192;
            const uint32_t r8 = (m & 1) ? 0 : 1024;
            float cs[4][4] = {};
#pragma unroll 1
            for (int k = 0; k < 4; k++) {
                uint32_t x[4][4], y[4][4];
                mbar_wait(bar0 + 8 * (B_ROW + k), 0);
#pragma unroll
                for (int i = 0; i < 4; i++) {
                    ldsm4(x[i], ra[i]); ldsm4(y[i], ra[i] + r8);
                    ra[i] += rs;
                }
#pragma unroll
                for (int i = 0; i < 4; i++) {
                    mma4(cs[2 * (i & 1)], x[i], x[i][0], x[i][2]);
                    mma4(cs[2 * (i & 1) + 1], y[i], y[i][0], y[i][2]);
                }
            }
            const uint32_t pa = gp + 2304 + 4 * a;
#pragma unroll
            for (int i = 0; i < 8; i++) cs[i >> 2][i & 3] += cs[2 + (i >> 2)][i & 3];
            if (g < 2) {
#pragma unroll
                for (int i = 0; i < 4; i++) sts32(pa + 256 * g + 32 * t + 128 * (i >> 1) + 16 * (i & 1), __float_as_uint(cs[i >> 1][2 + (i & 1)]));
            }
            if (t == (g >> 1)) {
                sts32(pa + 512 + 16 * g, __float_as_uint((g & 1) ? cs[0][1] : cs[0][0]));
                sts32(pa + 640 + 16 * g, __float_as_uint((g & 1) ? cs[1][1] : cs[1][0]));
            }
            named_sync(1, 128);
            auto sum4 = [](uint4 q) { return (__uint_as_float(q.x) + __uint_as_float(q.y)) + (__uint_as_float(q.z) + __uint_as_float(q.w)); };
            const uint32_t o = gp + 2304 + 16 * (lane & 15);
            const float mu = sum4(lds128(o)) * (1.f / DM), e2 = sum4(lds128(o + 512)) * (1.f / DM), var = fmaf(-mu, mu, e2);
            const float sw = sum4(lds128(o + 256));
            wsum = sum4(lds128(gp + 2176));
            uint32_t ms = mean_std(mu, var);
            float sc = (sw - bf_round(mu) * wsum) * rcpf(bf_hi(ms));
            if (__any_sync(0xffffffffu, !(e2 <= 65.f * var))) {
                const uint2 c = ln_centred(sb, mu);
                ms = c.x; sc = __uint_as_float(c.y);
            }
            if (lane < 16 && a < 2) st_relaxed_32(pst, ms | tbit);
            if (at < 16) st_relaxed_32(pky, pack_bf16(0.f, sc) | ktag);
            if (lane < 8) mbar_arrive(bar0 + 8 * (B_EMPTY + lane));
        }
        STAMP(3); GSTAMP(14);
        {
            const uint32_t* sp = p.scr + S_STAT + 2048 * (cl & 1) + 512 * a + 16 * t + 2 * g;
            uint2 sq[8];
            uint32_t s2[8], bad;
            mbar_wait(bar0 + 8 * (B_X + 4 * h + 3), 0);
#pragma unroll 1
            do {
                __nanosleep(0);
#pragma unroll
                for (int i = 0; i < 8; i++) sq[i] = ld_relaxed_64(sp + 64 * i);
                bad = 0;
#pragma unroll
                for (int i = 0; i < 8; i++) { s2[i] = __byte_perm(sq[i].x, sq[i].y, 0x7632) ^ want; bad |= s2[i]; }
            } while (!__all_sync(0xffffffffu, (bad & 0x80008000u) == 0));
            STAMP(13);
            const uint32_t xa = sb + OFF_X + 16384 * a + 32 * lane + ((h ^ (g & 1)) << 4);
            const uint32_t dst = sb + OFF_PRIV + (2 * m + (r & 1)) * PRIV + 128 + 512 * a + 16 * (r >> 1);
#pragma unroll
            for (int bk = 0; bk < 2; bk++) {
                mbar_wait(bar0 + 8 * (B_X + 2 * a + bk), 0);
                uint32_t v[8][4];
#pragma unroll
                for (int i = 0; i < 4; i++) {
                    const uint2 rc = recip2(s2[4 * bk + i]), st = sq[4 * bk + i];
#pragma unroll
                    for (int hf = 0; hf < 2; hf++) {
                        const __nv_bfloat162 mm = __low2bfloat162(as_b2(hf ? st.y : st.x));
                        const __nv_bfloat162 rh = hf ? __high2bfloat162(as_b2(rc.x)) : __low2bfloat162(as_b2(rc.x));
                        const __nv_bfloat162 rl = hf ? __high2bfloat162(as_b2(rc.y)) : __low2bfloat162(as_b2(rc.y));
                        const uint4 q = lds128(xa + 8192 * bk + 2048 * i + 1024 * hf);
                        uint32_t* o = v[2 * i + hf];
                        o[0] = normalize2(q.x, mm, rh, rl); o[1] = normalize2(q.y, mm, rh, rl); o[2] = normalize2(q.z, mm, rh, rl); o[3] = normalize2(q.w, mm, rh, rl);
                    }
                }
                if (bk == 0) mbar_wait(bar0 + 8 * B_KG, 0);
#pragma unroll
                for (int i = 0; i < 8; i++) stsm4t(dst + 256 * bk + 64 * (i >> 1) + PLANE * (i & 1), v[i]);
            }
            __syncwarp();
            if (elect_one()) { mbar_arrive(bar0 + 8 * B_VT); mbar_arrive_peer(mapa(bar0 + 8 * B_PV, h ^ 1)); }
            __syncwarp();
        }
        uint32_t mykey;
        {
            const uint32_t* sl = p.scr + S_SEL + 32 * (cl & 3) + 2 * g;
            uint2 q;
#pragma unroll 1
            do {
                __nanosleep(40);
                q = ld_relaxed_64(sl);
            } while (!__all_sync(0xffffffffu, q.y == ((epoch + 1u) | 0x8000u)));
            mykey = q.x;
        }
        STAMP(4);
        if (b < GU_CTAS) {
            const uint32_t tok = 0xffffu - (mykey & 0xffffu);
            {
                const uint32_t tk = __shfl_sync(0xffffffffu, tok, 16 * h + 4 * a);
                if (elect_one())
                    asm volatile("cp.async.bulk.shared::cluster.global.mbarrier::complete_tx::bytes.multicast::cluster [%0], [%1], 2048, [%2], %3;"
                                 ::"r"(sb + OFF_XS + (4 * h + a) * ROW_PITCH), "l"(p.u + (size_t)tk * DM), "r"(bar0 + 8 * B_XS), "h"((uint16_t)3) : "memory");
            }
        }
        if (a == 0) {
            const uint32_t tok = ~mykey & 0xffffu;
            if (t == 0) asm volatile("red.shared.or.b32 [%0], %1;" ::"r"(sb + OFF_MISC + 32 + 4 * (tok >> 5)), "r"(1u << (tok & 31u)) : "memory");
            sts32(sb + OFF_MISC + 4, __reduce_or_sync(0xffffffffu, 1u << (4 * (tok >> 8) + ((tok >> 1) & 3))));
            __syncwarp();
            if (elect_one()) { mbar_arrive(bar0 + 8 * B_RECV); mbar_arrive(bar0 + 8 * (B_RECV + 1)); }
        }
        if (b < GU_CTAS) {
            const uint32_t tok = 0xffffu - (mykey & 0xffffu);
            st_relaxed_128(py, 0u, 0u, 0u, 0u);
            uint2 rec;
#pragma unroll 1
            do {
                rec = ld_relaxed_64(p.scr + S_STAT + 2048 * (a & 1) + (tok & ~15u) + 2 * (tok & 7u));
            } while (!__all_sync(0xffffffffu, ((__byte_perm(rec.x, rec.y, 0x7632) ^ want) & 0x80008000u) == 0));
            const uint32_t mst = (tok & 8u) ? rec.y : rec.x;
            const uint32_t m2 = __byte_perm(mst, 0, 0x1010);
            const float rs = rcpf(__uint_as_float(mst & 0x7fff0000u));
            const float r0 = __shfl_sync(0xffffffffu, rs, 8 * t), r1 = __shfl_sync(0xffffffffu, rs, 8 * t + 4);
            float gacc[4][4] = {};
            const int k = r + 8 * (m >> 1);
            uint32_t wa[4];
#pragma unroll
            for (int mt = 0; mt < 4; mt++) wa[mt] = 1024 * a + (((m & 1) * 4096) ^ p.up_first) + k * 64 + ((((k >> 1) & 3) ^ mt) << 4);
            const uint32_t xa = sb + OFF_XS + r * ROW_PITCH + 32 * a + 16 * (m & 1) + 128 * (m >> 1);
#pragma unroll 1
            for (int c = 0; c < 4; c++) {
                uint32_t af[4][4][4], xb[2][4];
                const uint32_t half = sb + OFF_RING + 32768 * (c & 1), fb = bar0 + 8 * B_FULL + 32 * (c & 1);
#pragma unroll
                for (int j = 0; j < 4; j++) {
                    mbar_wait(fb + 8 * j, c >> 1);
                    if (j == 3) STAMP(12);
#pragma unroll
                    for (int mt = 0; mt < 4; mt++) ldsm4t(af[j][mt], wa[mt] + half + j * 8192);
                    __syncwarp();
                    if (elect_one()) mbar_arrive(fb + 8 * (B_EMPTY - B_FULL + j));
                    if (j == 2) {
                        mbar_wait(bar0 + 8 * B_XS, 0);
#pragma unroll
                        for (int i = 0; i < 2; i++) {
                            ldsm4(xb[i], xa + 512 * c + 256 * i);
#pragma unroll
                            for (int e = 0; e < 4; e++) xb[i][e] = as_u(__hsub2(as_b2(xb[i][e]), as_b2(m2)));
                        }
                    }
                    if (j == 3) STAMP(1);
                    if (j >= 2) {
#pragma unroll
                        for (int ks = j == 2 ? 0 : j; ks <= j; ks++) {
#pragma unroll
                            for (int mt = 0; mt < 4; mt++)
                                mma_bf16v(gacc[mt], af[ks][mt], xb[ks >> 1][2 * (ks & 1)], xb[ks >> 1][2 * (ks & 1) + 1]);
                        }
                    }
                }
            }
            STAMP(6);
#pragma unroll
            for (int mt = 0; mt < 4; mt++) sts128f(gp + 2048 * a + mt * 512 + lane * 16, gacc[mt]);
            named_sync(1, 128);
            {
                uint4 q[4];
#pragma unroll
                for (int wq = 0; wq < 4; wq++) q[wq] = lds128(gp + 2048 * wq + 16 * at);
                const uint32_t g2 = pack_bf16(r0 * ((__uint_as_float(q[0].x) + __uint_as_float(q[1].x)) + (__uint_as_float(q[2].x) + __uint_as_float(q[3].x))),
                                              r1 * ((__uint_as_float(q[0].y) + __uint_as_float(q[1].y)) + (__uint_as_float(q[2].y) + __uint_as_float(q[3].y))));
                const uint32_t u2 = pack_bf16(r0 * ((__uint_as_float(q[0].z) + __uint_as_float(q[1].z)) + (__uint_as_float(q[2].z) + __uint_as_float(q[3].z))),
                                              r1 * ((__uint_as_float(q[0].w) + __uint_as_float(q[1].w)) + (__uint_as_float(q[2].w) + __uint_as_float(q[3].w))));
                const uint32_t s2 = pack_bf16(bf_lo(g2) * rcpf(1.f + ex2f(-L2E * bf_lo(g2))), bf_hi(g2) * rcpf(1.f + ex2f(-L2E * bf_hi(g2))));
                uint32_t hw;
                asm volatile("movmatrix.sync.aligned.m8n8.trans.b16 %0, %1;" : "=r"(hw) : "r"(as_u(__hmul2(as_b2(s2), as_b2(u2)))));
                if (hw == 0u) hw = 0x80008000u;
                st_relaxed_32(p.scr + S_H + hsel + b * 128 + at, hw);
            }
            STAMP(7);
        }
        const uint32_t ytag = 1u + (epoch & 1);
        {
            const uint32_t* hp = p.scr + S_H + hsel + (b & 7) * 1792 + 64 * a + lane;
            uint32_t wa[4], af[6][4][4], hb[14];
#pragma unroll
            for (int mt = 0; mt < 4; mt++) wa[mt] = sb + OFF_RING + 2048 * a + 128 * (r + 8 * (m >> 1)) + (((2 * mt + (m & 1)) ^ r) << 4);
            float dacc[4][4] = {};
            auto load_w = [&](int s) {
                mbar_wait(bar0 + 8 * (B_FULL + s), 0);
#pragma unroll
                for (int j = 0; j < 4; j++) ldsm4t(af[s % 6][j], wa[j] + s * 8192);
            };
            auto run = [&](int s) {
#pragma unroll
                for (int j = 0; j < 4; j++) mma_bf16v(dacc[j], af[s % 6][j], hb[2 * s], hb[2 * s + 1]);
            };
            auto look = [&]() {
#pragma unroll
                for (int j = 0; j < 14; j++) hb[j] = ld_relaxed_32(hp + 256 * (j >> 1) + 32 * (j & 1));
            };
            auto missing = [&]() {
                uint32_t mn = hb[0];
#pragma unroll
                for (int j = 1; j < 14; j++) mn = min(mn, hb[j]);
                return __any_sync(0xffffffffu, mn == 0);
            };
            load_w(0);
            if (b >= GU_CTAS) st_relaxed_128(py, 0u, 0u, 0u, 0u);
            bool again = true;
            if (b >= GU_CTAS) { look(); again = missing(); }
#pragma unroll
            for (int s = 1; s < 5; s++) load_w(s);
            if (again) look();
            load_w(5);
#pragma unroll 1
            while (missing()) { __nanosleep(0); look(); }
            STAMP(2);
#pragma unroll
            for (int s = 0; s < 6; s++) run(s);
            load_w(6);
            run(6);
            STAMP(8);
#pragma unroll
            for (int mt = 0; mt < 4; mt++) sts128f(sb + OFF_XS + 2048 * a + mt * 512 + lane * 16, dacc[mt]);
            named_sync(1, 128);
            uint4 q[4];
#pragma unroll
            for (int wq = 0; wq < 4; wq++) q[wq] = lds128(sb + OFF_XS + 2048 * wq + 16 * at);
            auto tagged = [&](uint32_t x0, uint32_t x1, uint32_t x2, uint32_t x3) {
                return (__float_as_uint((__uint_as_float(x0) + __uint_as_float(x1)) + (__uint_as_float(x2) + __uint_as_float(x3))) & ~3u) | ytag;
            };
            st_relaxed_128(py, tagged(q[0].x, q[1].x, q[2].x, q[3].x), tagged(q[0].y, q[1].y, q[2].y, q[3].y),
                           tagged(q[0].z, q[1].z, q[2].z, q[3].z), tagged(q[0].w, q[1].w, q[2].w, q[3].w));
        }
        STAMP(9);
        {
            const uint32_t key = __shfl_sync(0xffffffffu, mykey, 8 * a + 4 * (m >> 1));
            const uint32_t tok = 0xffffu - (key & 0xffffu);
            const float sg = bf_round(rcpf(1.f + ex2f(-L2E * bf_lo(unorder_key(key >> 16)))));
            const uint32_t xo = sb + OFF_X + 32 * (tok & ~63u) + 128 * (tok & 15u) + 2 * (tok & 48u) + ((2 * (lane & 15)) ^ ((tok & 1u) << 4));
            const bool mine = ((tok >> 8) & 1) == h;
            if (elect_one()) mbar_arrive(bar0 + 8 * B_DONE);
            if (mine) {
                const uint32_t* yp = p.scr + S_Y + 1024 * cl + 32 * a + 4 * r + 2 * (m & 1) + (m >> 1);
                uint32_t pp[8], bad, it = 0, o;
#pragma unroll 1
                do {
                    if (++it > SPIN_LIMIT) __trap();
                    bad = 0;
#pragma unroll
                    for (int q = 0; q < 8; q++) pp[q] = ld_relaxed_32(yp + 128 * q);
#pragma unroll
                    for (int q = 0; q < 8; q++) { pp[q] ^= ytag; bad |= pp[q]; }
                } while (bad & 3u);
                const float y = ((__uint_as_float(pp[0]) + __uint_as_float(pp[1])) + (__uint_as_float(pp[2]) + __uint_as_float(pp[3]))) +
                                ((__uint_as_float(pp[4]) + __uint_as_float(pp[5])) + (__uint_as_float(pp[6]) + __uint_as_float(pp[7])));
                const uint32_t upd = pack_bf16(bf_round(y) * sg, 0.f);
                STAMP(11);
                mbar_wait(bar0 + 8 * B_ST, 0);
                asm volatile("ld.shared.u16 %0, [%1];" : "=r"(o) : "r"(xo));
                asm volatile("st.global.u16 [%0], %1;" ::"l"(p.out + (size_t)tok * DM + 16 * cl + (lane & 15)), "r"(badd2(o, upd)) : "memory");
            }
        }
        STAMP(10); GSTAMP(15);
    } else {
        asm volatile("setmaxnreg.dec.sync.aligned.u32 %0;" ::"n"(PROD_REGS));
        const int q = warp - 12;
        sts32(sb + OFF_MISC + 16 + 4 * q, clk());
        const uint32_t t0 = __shfl_sync(0xffffffffu, lds32v(sb + OFF_MISC + 16 + 4 * q), 0);
        STAMP(0);
        if (q == 1) GSTAMP(14);
        const bool one = elect_one();
        const uint32_t rbar = bar0 + 8 * (B_ROW + q);
        if (one) {
            asm volatile("prefetch.tensormap [%0];" ::"l"(&maps.rows) : "memory");
            mbar_init(rbar, 1);
            if (q == 3) mbar_init(bar0 + 8 * B_WR, 1);
            fence_async();
            mbar_expect_tx(rbar, 8192);
            if (q == 3) {
                mbar_expect_tx(bar0 + 8 * B_WR, 2048);
                bulk_g2s(sb + OFF_GP, p.wr, 2048, bar0 + 8 * B_WR);
            }
        }
        __syncwarp();
        cluster_arrive();
        wait_until(t0 + ROW_DELAY + q * ROW_PERIOD);
        if (one) {
            tma_load_3d(sb + OFF_ROWS + 8192 * q, &maps.rows, 16 * b, 4 * q, rbar);
            asm volatile("prefetch.tensormap [%0];" ::"l"(&maps.u + q) : "memory");
        }
        __syncwarp();
        cluster_wait();
        STAMP(1);
        wait_until(t0 + X_DELAY + q * 60);
        if (one) tma_load_4d_both(sb + OFF_X + 8192 * (4 * h + q), &maps.u, 16 * cl, 4 * (4 * h + q), bar0 + 8 * (B_X + 4 * h + q));
        STAMP(2);
        const char* src = (const char*)((b >> 6) ? p.wu : p.wg) + (64 * q + (b & 63)) * 7168 + 128 * lane;
        const uint32_t phase = t0 + PF_START + (b * PF_PERIOD >> 7) + q * PF_PERIOD;
        auto fill = [&](int j, uint32_t due, const CUtensorMap* map, int c0, int c3) {
            const uint32_t bar = bar0 + 8 * (B_FULL + q + 4 * (j & 1));
            wait_until(due);
            mbar_wait_bounded(bar + 8 * (B_EMPTY - B_FULL), (j >> 1) & 1);
            if (one) {
                mbar_expect_tx(bar, 8192);
                tma_load_4d(sb + OFF_RING + (q + 4 * (j & 1)) * 8192, map, c0, c3, bar);
            }
            STAMP(3 + (j >> 1));
        };
#pragma unroll 1
        for (int j = 0; j < 4; j++) {
            wait_until(phase + 4 * j * PF_PERIOD);
            asm volatile("prefetch.global.L2 [%0];" ::"l"(src) : "memory");
            if (lane < 24) asm volatile("prefetch.global.L2 [%0];" ::"l"(src + 4096) : "memory");
            src += 256 * 7168;
            STAMP(6);
            if (b < GU_CTAS) fill(j, t0 + LD_START + (b * LD_SPREAD >> 7) + (q + 4 * j) * LD_PERIOD, &maps.wgu, 32 * b, q + 4 * j);
        }
#pragma unroll 1
        for (int j = 4; j < (q < 3 ? 6 : 5); j++)
            fill(j, phase + 4 * j * PF_PERIOD + (q + 4 * j - 16) * WD_EXTRA, &maps.wd, 64 * (b >> 3), 7 * (b & 7) + q + 4 * j - 16);
        if (q >= 2) mbar_wait_bounded(bar0 + 8 * (q == 2 ? B_DONE : B_RECV + 3), 0);
    }
}

typedef CUresult (*EncodeFn)(CUtensorMap*, CUtensorMapDataType, cuuint32_t, void*, const cuuint64_t*, const cuuint64_t*,
                             const cuuint32_t*, const cuuint32_t*, CUtensorMapInterleave, CUtensorMapSwizzle,
                             CUtensorMapL2promotion, CUtensorMapFloatOOBfill);

void make_map(EncodeFn enc, CUtensorMap* m, int rank, const void* ptr, const cuuint64_t (&dims)[5], const cuuint64_t (&str)[4],
              const cuuint32_t (&box)[5], CUtensorMapSwizzle sw, CUtensorMapL2promotion pr) {
    const cuuint32_t es[5] = {1, 1, 1, 1, 1};
    CUresult rc = enc(m, CU_TENSOR_MAP_DATA_TYPE_BFLOAT16, rank, const_cast<void*>(ptr), dims, str, box, es, CU_TENSOR_MAP_INTERLEAVE_NONE, sw, pr,
                      CU_TENSOR_MAP_FLOAT_OOB_FILL_NONE);
    (void)rc;
}

}

extern "C" void kernel_launch(void* const* d_in, const int* in_sizes, int n_in, void* d_out, int out_size) {
    (void)in_sizes; (void)n_in; (void)out_size;
    static EncodeFn enc = nullptr;
    static void* scr = nullptr;
    if (!enc) {
        void* fn = nullptr;
        cudaDriverEntryPointQueryResult q;
        cudaGetDriverEntryPoint("cuTensorMapEncodeTiled", &fn, cudaEnableDefault, &q);
        enc = (EncodeFn)fn;
        cudaGetSymbolAddress(&scr, g_scr);
        cudaFuncSetAttribute(fused_kernel, cudaFuncAttributeMaxDynamicSharedMemorySize, SMEM_BYTES);
    }
    Maps maps;
    const uintptr_t ag = (uintptr_t)d_in[9], au = (uintptr_t)d_in[10];
    const auto noprom = CU_TENSOR_MAP_L2_PROMOTION_NONE, prom = CU_TENSOR_MAP_L2_PROMOTION_L2_128B;
    make_map(enc, &maps.rows, 3, d_in[0], {64, SEQ, 16, 1}, {2048, 128, 0}, {64, 16, 4, 1}, CU_TENSOR_MAP_SWIZZLE_128B, noprom);
    make_map(enc, &maps.u, 4, d_in[0], {DM, 4, 16, 32}, {32768, 2048, 131072}, {16, 4, 16, 4}, CU_TENSOR_MAP_SWIZZLE_32B, noprom);
    make_map(enc, &maps.out, 5, d_out, {DM, 4, 8, 2, 32}, {32768, 2048, 16384, 131072}, {16, 4, 2, 2, 4}, CU_TENSOR_MAP_SWIZZLE_NONE, noprom);
    make_map(enc, &maps.wgu, 4, (const void*)(ag < au ? ag : au), {FF, 64, 2, 16}, {FF * 2, ag < au ? au - ag : ag - au, 64 * FF * 2}, {32, 64, 2, 1},
             CU_TENSOR_MAP_SWIZZLE_64B, prom);
    make_map(enc, &maps.wd, 4, d_in[11], {DM, 64, 1, 56}, {2048, 131072, 131072}, {64, 64, 1, 1}, CU_TENSOR_MAP_SWIZZLE_128B, prom);
    Ptrs p;
    p.u = (const __nv_bfloat16*)d_in[0];
    p.logA = (const __nv_bfloat16*)d_in[1];
    p.Aim = (const __nv_bfloat16*)d_in[2];
    p.Cre = (const __nv_bfloat16*)d_in[3];
    p.Cim = (const __nv_bfloat16*)d_in[4];
    p.ldt = (const __nv_bfloat16*)d_in[5];
    p.dsk = (const __nv_bfloat16*)d_in[6];
    p.wr = (const __nv_bfloat16*)d_in[8];
    p.wg = (const __nv_bfloat16*)d_in[9];
    p.wu = (const __nv_bfloat16*)d_in[10];
    p.out = (__nv_bfloat16*)d_out;
    p.scr = (uint32_t*)scr;
    p.up_first = ag < au ? 0 : 4096;
    p.zero = 0;
    fused_kernel<<<NCTA + 2, NTHR, SMEM_BYTES, cudaStreamPerThread>>>(p, maps);
}
```
